```python
import torch

def _softmax(x, axis=-1):
    return torch.softmax(x, dim=axis)
def _gelu(x):
    return torch.nn.functional.gelu(x, approximate="tanh")
def _silu(x):
    return torch.nn.functional.silu(x)
def _sigmoid(x):
    return torch.sigmoid(x)
def _layernorm(x, axis=-1, eps=1e-5):
    m = x.mean(dim=axis, keepdim=True)
    v = x.var(dim=axis, keepdim=True, unbiased=False)
    return (x - m) / torch.sqrt(v + eps)
def _scatter_add(tgt, idx, src, axis=0):
    return tgt.clone().index_add_(axis, idx, src)
def _segment_sum(src, seg, n):
    out = torch.zeros((n,) + src.shape[1:], dtype=src.dtype)
    return out.index_add_(0, seg, src)
def _pad(x, pw):
    flat = tuple(v for pair in reversed(pw) for v in pair)
    return torch.nn.functional.pad(x, flat)

kernel_name = 'gated_mix__linear_kernel_hedgehog__ssm_conv_s4d__prompt'

def setup_inputs():

    _w = (lambda a: (lambda t: t.to(torch.bfloat16) if t.is_floating_point() else t)(torch.as_tensor(a)))
    def _A_setup():
        B, S, D, H = 1, 2048, 640, 32
        Dh = D // H
        return {
            "x": _w((lambda *s: torch.randn(*s, dtype=torch.bfloat16) * 0.05)(B, S, D)),
            "wqkv": _w((lambda *s: torch.randn(*s, dtype=torch.bfloat16) * 0.8)(D, 3 * D)),
            "w_phi": _w((lambda *s: torch.randn(*s, dtype=torch.bfloat16) * 0.8)(H, Dh, Dh) * (Dh ** -0.5)),
            "wo": _w((lambda *s: torch.randn(*s, dtype=torch.bfloat16) * 0.05)(D, D)),
        }
    _A_in = _A_setup()

    def _B_setup():
        Bsz, L, D, N = 1, 2048, 640, 128
        return {
            "u": _w((lambda *s: torch.randn(*s, dtype=torch.bfloat16) * 0.05)(Bsz, L, D)),
            "log_A_real": _w((lambda *s: torch.randn(*s, dtype=torch.bfloat16) * 6.4)(D, N) * 0.5),
            "A_imag": _w((lambda *s: torch.randn(*s, dtype=torch.bfloat16) * 0.05)(D, N) * 3.14),
            "C_real": _w((lambda *s: torch.randn(*s, dtype=torch.bfloat16) * 0.2)(D, N) / N ** 0.5),
            "C_imag": _w((lambda *s: torch.randn(*s, dtype=torch.bfloat16) * 0.2)(D, N) / N ** 0.5),
            "log_dt": _w((lambda *s: torch.randn(*s, dtype=torch.bfloat16) * 0.05)(D) * 0.5 - 4.0),
            "D_skip": _w((lambda *s: torch.randn(*s, dtype=torch.bfloat16) * 0.05)(D)),
        }
    _B_in = _B_setup()

    return {
        "A_x": _A_in["x"],
        "A_wqkv": _A_in["wqkv"],
        "A_w_phi": _A_in["w_phi"],
        "A_wo": _A_in["wo"],
        "B_u": _B_in["u"],
        "B_log_A_real": _B_in["log_A_real"],
        "B_A_imag": _B_in["A_imag"],
        "B_C_real": _B_in["C_real"],
        "B_C_imag": _B_in["C_imag"],
        "B_log_dt": _B_in["log_dt"],
        "B_D_skip": _B_in["D_skip"],
        "gate_w": _w((lambda *s: torch.randn(*s, dtype=torch.bfloat16) * 0.05)(640) * 16.0),
    }

def reference(A_x, A_wqkv, A_w_phi, A_wo, B_u, B_log_A_real, B_A_imag, B_C_real, B_C_imag, B_log_dt, B_D_skip, gate_w):
    def _A_ref(x, wqkv, w_phi, wo):
        B, S, D = x.shape
        H = 32; Dh = D // H
        qkv = (lambda x, *d: x.permute(*d))((x @ wqkv).reshape(B, S, 3, H, Dh), 2, 0, 3, 1, 4)
        q, k, v = qkv[0], qkv[1], qkv[2]
        pq = torch.einsum("bhsd,hdf->bhsf", q, w_phi)
        pk = torch.einsum("bhsd,hdf->bhsf", k, w_phi)
        phi_q = torch.concatenate([_softmax(pq, axis=-1), _softmax(-pq, axis=-1)], axis=-1)
        phi_k = torch.concatenate([_softmax(pk, axis=-1), _softmax(-pk, axis=-1)], axis=-1)
        kv = torch.einsum("bhsf,bhsd->bhfd", phi_k, v)
        z  = torch.einsum("bhsf->bhf", phi_k)
        num = torch.einsum("bhqf,bhfd->bhqd", phi_q, kv)
        den = torch.einsum("bhqf,bhf->bhq", phi_q, z)[..., None] + 1e-6
        o = num / den
        return (lambda x, *d: x.permute(*d))(o, 0, 2, 1, 3).reshape(B, S, D) @ wo

    def _B_ref(u, log_A_real, A_imag, C_real, C_imag, log_dt, D_skip):
        L = u.shape[1]
        dt = torch.exp(log_dt)
        A = -torch.exp(log_A_real) + 1j * A_imag
        C = (C_real + 1j * C_imag) * dt[:, None]
        pos = (lambda x, dt: x.to(dt))(torch.arange(L), log_dt.dtype)
        P = torch.exp((A * dt[:, None])[:, :, None] * pos[None, None, :])
        K = 2.0 * torch.einsum("dn,dnl->dl", C, P).real
        L2 = 2 * L
        u_t = (lambda x, *d: x.permute(*d))(u, 0, 2, 1)
        Kf = (lambda x, *a, **k: torch.fft.rfft(x.float(), *a, **k))(K, L2)
        Uf = (lambda x, *a, **k: torch.fft.rfft(x.float(), *a, **k))(u_t, L2)
        y = (lambda x, *a, **k: torch.fft.irfft(x, *a, **k).to(torch.bfloat16))(Uf * Kf[None, :, :], L2)[:, :, :L]
        y = (lambda x, *d: x.permute(*d))(y, 0, 2, 1)
        return y + u * D_skip[None, None, :]

    x = A_x
    g = _sigmoid((x * gate_w).sum(-1, keepdims=True))
    a = _A_ref(x, A_wqkv, A_w_phi, A_wo)
    b = _B_ref(x, B_log_A_real, B_A_imag, B_C_real, B_C_imag, B_log_dt, B_D_skip)
    return g * a + (1 - g) * b
```

```cpp
#include <cuda_runtime.h>
#include <cuda_bf16.h>
#include <cuda.h>
#include <stdint.h>

template<int N, int TA, int TB> __device__ __forceinline__ void wgmma_ss(float* d, uint64_t da, uint64_t db, int sd);
template<int N, int TB> __device__ __forceinline__ void wgmma_rs(float* d, uint32_t a0, uint32_t a1, uint32_t a2, uint32_t a3, uint64_t db, int sd);
template<> __device__ __forceinline__ void wgmma_ss<192,0,1>(float* d, uint64_t da, uint64_t db, int sd) {
  asm volatile("{\n.reg .pred p;\nsetp.ne.b32 p, %98, 0;\n"
  "wgmma.mma_async.sync.aligned.m64n192k16.f32.bf16.bf16 {%0,%1,%2,%3,%4,%5,%6,%7,%8,%9,%10,%11,%12,%13,%14,%15,%16,%17,%18,%19,%20,%21,%22,%23,%24,%25,%26,%27,%28,%29,%30,%31,%32,%33,%34,%35,%36,%37,%38,%39,%40,%41,%42,%43,%44,%45,%46,%47,%48,%49,%50,%51,%52,%53,%54,%55,%56,%57,%58,%59,%60,%61,%62,%63,%64,%65,%66,%67,%68,%69,%70,%71,%72,%73,%74,%75,%76,%77,%78,%79,%80,%81,%82,%83,%84,%85,%86,%87,%88,%89,%90,%91,%92,%93,%94,%95}, %96, %97, p, 1, 1, 0, 1;\n}\n"
  : "+f"(d[0]),"+f"(d[1]),"+f"(d[2]),"+f"(d[3]),"+f"(d[4]),"+f"(d[5]),"+f"(d[6]),"+f"(d[7]),"+f"(d[8]),"+f"(d[9]),"+f"(d[10]),"+f"(d[11]),"+f"(d[12]),"+f"(d[13]),"+f"(d[14]),"+f"(d[15]),"+f"(d[16]),"+f"(d[17]),"+f"(d[18]),"+f"(d[19]),"+f"(d[20]),"+f"(d[21]),"+f"(d[22]),"+f"(d[23]),"+f"(d[24]),"+f"(d[25]),"+f"(d[26]),"+f"(d[27]),"+f"(d[28]),"+f"(d[29]),"+f"(d[30]),"+f"(d[31]),"+f"(d[32]),"+f"(d[33]),"+f"(d[34]),"+f"(d[35]),"+f"(d[36]),"+f"(d[37]),"+f"(d[38]),"+f"(d[39]),"+f"(d[40]),"+f"(d[41]),"+f"(d[42]),"+f"(d[43]),"+f"(d[44]),"+f"(d[45]),"+f"(d[46]),"+f"(d[47]),"+f"(d[48]),"+f"(d[49]),"+f"(d[50]),"+f"(d[51]),"+f"(d[52]),"+f"(d[53]),"+f"(d[54]),"+f"(d[55]),"+f"(d[56]),"+f"(d[57]),"+f"(d[58]),"+f"(d[59]),"+f"(d[60]),"+f"(d[61]),"+f"(d[62]),"+f"(d[63]),"+f"(d[64]),"+f"(d[65]),"+f"(d[66]),"+f"(d[67]),"+f"(d[68]),"+f"(d[69]),"+f"(d[70]),"+f"(d[71]),"+f"(d[72]),"+f"(d[73]),"+f"(d[74]),"+f"(d[75]),"+f"(d[76]),"+f"(d[77]),"+f"(d[78]),"+f"(d[79]),"+f"(d[80]),"+f"(d[81]),"+f"(d[82]),"+f"(d[83]),"+f"(d[84]),"+f"(d[85]),"+f"(d[86]),"+f"(d[87]),"+f"(d[88]),"+f"(d[89]),"+f"(d[90]),"+f"(d[91]),"+f"(d[92]),"+f"(d[93]),"+f"(d[94]),"+f"(d[95]) : "l"(da), "l"(db), "r"(sd));
}
template<> __device__ __forceinline__ void wgmma_ss<48,0,1>(float* d, uint64_t da, uint64_t db, int sd) {
  asm volatile("{\n.reg .pred p;\nsetp.ne.b32 p, %26, 0;\n"
  "wgmma.mma_async.sync.aligned.m64n48k16.f32.bf16.bf16 {%0,%1,%2,%3,%4,%5,%6,%7,%8,%9,%10,%11,%12,%13,%14,%15,%16,%17,%18,%19,%20,%21,%22,%23}, %24, %25, p, 1, 1, 0, 1;\n}\n"
  : "+f"(d[0]),"+f"(d[1]),"+f"(d[2]),"+f"(d[3]),"+f"(d[4]),"+f"(d[5]),"+f"(d[6]),"+f"(d[7]),"+f"(d[8]),"+f"(d[9]),"+f"(d[10]),"+f"(d[11]),"+f"(d[12]),"+f"(d[13]),"+f"(d[14]),"+f"(d[15]),"+f"(d[16]),"+f"(d[17]),"+f"(d[18]),"+f"(d[19]),"+f"(d[20]),"+f"(d[21]),"+f"(d[22]),"+f"(d[23]) : "l"(da), "l"(db), "r"(sd));
}
template<> __device__ __forceinline__ void wgmma_rs<80,1>(float* d, uint32_t a0, uint32_t a1, uint32_t a2, uint32_t a3, uint64_t db, int sd) {
  asm volatile("{\n.reg .pred p;\nsetp.ne.b32 p, %45, 0;\n"
  "wgmma.mma_async.sync.aligned.m64n80k16.f32.bf16.bf16 {%0,%1,%2,%3,%4,%5,%6,%7,%8,%9,%10,%11,%12,%13,%14,%15,%16,%17,%18,%19,%20,%21,%22,%23,%24,%25,%26,%27,%28,%29,%30,%31,%32,%33,%34,%35,%36,%37,%38,%39}, {%40,%41,%42,%43}, %44, p, 1, 1, 1;\n}\n"
  : "+f"(d[0]),"+f"(d[1]),"+f"(d[2]),"+f"(d[3]),"+f"(d[4]),"+f"(d[5]),"+f"(d[6]),"+f"(d[7]),"+f"(d[8]),"+f"(d[9]),"+f"(d[10]),"+f"(d[11]),"+f"(d[12]),"+f"(d[13]),"+f"(d[14]),"+f"(d[15]),"+f"(d[16]),"+f"(d[17]),"+f"(d[18]),"+f"(d[19]),"+f"(d[20]),"+f"(d[21]),"+f"(d[22]),"+f"(d[23]),"+f"(d[24]),"+f"(d[25]),"+f"(d[26]),"+f"(d[27]),"+f"(d[28]),"+f"(d[29]),"+f"(d[30]),"+f"(d[31]),"+f"(d[32]),"+f"(d[33]),"+f"(d[34]),"+f"(d[35]),"+f"(d[36]),"+f"(d[37]),"+f"(d[38]),"+f"(d[39]) : "r"(a0), "r"(a1), "r"(a2), "r"(a3), "l"(db), "r"(sd));
}
template<> __device__ __forceinline__ void wgmma_ss<32,1,1>(float* d, uint64_t da, uint64_t db, int sd) {
  asm volatile("{\n.reg .pred p;\nsetp.ne.b32 p, %18, 0;\n"
  "wgmma.mma_async.sync.aligned.m64n32k16.f32.bf16.bf16 {%0,%1,%2,%3,%4,%5,%6,%7,%8,%9,%10,%11,%12,%13,%14,%15}, %16, %17, p, 1, 1, 1, 1;\n}\n"
  : "+f"(d[0]),"+f"(d[1]),"+f"(d[2]),"+f"(d[3]),"+f"(d[4]),"+f"(d[5]),"+f"(d[6]),"+f"(d[7]),"+f"(d[8]),"+f"(d[9]),"+f"(d[10]),"+f"(d[11]),"+f"(d[12]),"+f"(d[13]),"+f"(d[14]),"+f"(d[15]) : "l"(da), "l"(db), "r"(sd));
}
template<> __device__ __forceinline__ void wgmma_rs<88,1>(float* d, uint32_t a0, uint32_t a1, uint32_t a2, uint32_t a3, uint64_t db, int sd) {
  asm volatile("{\n.reg .pred p;\nsetp.ne.b32 p, %49, 0;\n"
  "wgmma.mma_async.sync.aligned.m64n88k16.f32.bf16.bf16 {%0,%1,%2,%3,%4,%5,%6,%7,%8,%9,%10,%11,%12,%13,%14,%15,%16,%17,%18,%19,%20,%21,%22,%23,%24,%25,%26,%27,%28,%29,%30,%31,%32,%33,%34,%35,%36,%37,%38,%39,%40,%41,%42,%43}, {%44,%45,%46,%47}, %48, p, 1, 1, 1;\n}\n"
  : "+f"(d[0]),"+f"(d[1]),"+f"(d[2]),"+f"(d[3]),"+f"(d[4]),"+f"(d[5]),"+f"(d[6]),"+f"(d[7]),"+f"(d[8]),"+f"(d[9]),"+f"(d[10]),"+f"(d[11]),"+f"(d[12]),"+f"(d[13]),"+f"(d[14]),"+f"(d[15]),"+f"(d[16]),"+f"(d[17]),"+f"(d[18]),"+f"(d[19]),"+f"(d[20]),"+f"(d[21]),"+f"(d[22]),"+f"(d[23]),"+f"(d[24]),"+f"(d[25]),"+f"(d[26]),"+f"(d[27]),"+f"(d[28]),"+f"(d[29]),"+f"(d[30]),"+f"(d[31]),"+f"(d[32]),"+f"(d[33]),"+f"(d[34]),"+f"(d[35]),"+f"(d[36]),"+f"(d[37]),"+f"(d[38]),"+f"(d[39]),"+f"(d[40]),"+f"(d[41]),"+f"(d[42]),"+f"(d[43]) : "r"(a0), "r"(a1), "r"(a2), "r"(a3), "l"(db), "r"(sd));
}
template<> __device__ __forceinline__ void wgmma_ss<80,0,1>(float* d, uint64_t da, uint64_t db, int sd) {
  asm volatile("{\n.reg .pred p;\nsetp.ne.b32 p, %42, 0;\n"
  "wgmma.mma_async.sync.aligned.m64n80k16.f32.bf16.bf16 {%0,%1,%2,%3,%4,%5,%6,%7,%8,%9,%10,%11,%12,%13,%14,%15,%16,%17,%18,%19,%20,%21,%22,%23,%24,%25,%26,%27,%28,%29,%30,%31,%32,%33,%34,%35,%36,%37,%38,%39}, %40, %41, p, 1, 1, 0, 1;\n}\n"
  : "+f"(d[0]),"+f"(d[1]),"+f"(d[2]),"+f"(d[3]),"+f"(d[4]),"+f"(d[5]),"+f"(d[6]),"+f"(d[7]),"+f"(d[8]),"+f"(d[9]),"+f"(d[10]),"+f"(d[11]),"+f"(d[12]),"+f"(d[13]),"+f"(d[14]),"+f"(d[15]),"+f"(d[16]),"+f"(d[17]),"+f"(d[18]),"+f"(d[19]),"+f"(d[20]),"+f"(d[21]),"+f"(d[22]),"+f"(d[23]),"+f"(d[24]),"+f"(d[25]),"+f"(d[26]),"+f"(d[27]),"+f"(d[28]),"+f"(d[29]),"+f"(d[30]),"+f"(d[31]),"+f"(d[32]),"+f"(d[33]),"+f"(d[34]),"+f"(d[35]),"+f"(d[36]),"+f"(d[37]),"+f"(d[38]),"+f"(d[39]) : "l"(da), "l"(db), "r"(sd));
}
template<> __device__ __forceinline__ void wgmma_rs<16,0>(float* d, uint32_t a0, uint32_t a1, uint32_t a2, uint32_t a3, uint64_t db, int sd) {
  asm volatile("{\n.reg .pred p;\nsetp.ne.b32 p, %13, 0;\n"
  "wgmma.mma_async.sync.aligned.m64n16k16.f32.bf16.bf16 {%0,%1,%2,%3,%4,%5,%6,%7}, {%8,%9,%10,%11}, %12, p, 1, 1, 0;\n}\n"
  : "+f"(d[0]),"+f"(d[1]),"+f"(d[2]),"+f"(d[3]),"+f"(d[4]),"+f"(d[5]),"+f"(d[6]),"+f"(d[7]) : "r"(a0), "r"(a1), "r"(a2), "r"(a3), "l"(db), "r"(sd));
}
template<> __device__ __forceinline__ void wgmma_rs<32,0>(float* d, uint32_t a0, uint32_t a1, uint32_t a2, uint32_t a3, uint64_t db, int sd) {
  asm volatile("{\n.reg .pred p;\nsetp.ne.b32 p, %21, 0;\n"
  "wgmma.mma_async.sync.aligned.m64n32k16.f32.bf16.bf16 {%0,%1,%2,%3,%4,%5,%6,%7,%8,%9,%10,%11,%12,%13,%14,%15}, {%16,%17,%18,%19}, %20, p, 1, 1, 0;\n}\n"
  : "+f"(d[0]),"+f"(d[1]),"+f"(d[2]),"+f"(d[3]),"+f"(d[4]),"+f"(d[5]),"+f"(d[6]),"+f"(d[7]),"+f"(d[8]),"+f"(d[9]),"+f"(d[10]),"+f"(d[11]),"+f"(d[12]),"+f"(d[13]),"+f"(d[14]),"+f"(d[15]) : "r"(a0), "r"(a1), "r"(a2), "r"(a3), "l"(db), "r"(sd));
}
template<> __device__ __forceinline__ void wgmma_rs<48,0>(float* d, uint32_t a0, uint32_t a1, uint32_t a2, uint32_t a3, uint64_t db, int sd) {
  asm volatile("{\n.reg .pred p;\nsetp.ne.b32 p, %29, 0;\n"
  "wgmma.mma_async.sync.aligned.m64n48k16.f32.bf16.bf16 {%0,%1,%2,%3,%4,%5,%6,%7,%8,%9,%10,%11,%12,%13,%14,%15,%16,%17,%18,%19,%20,%21,%22,%23}, {%24,%25,%26,%27}, %28, p, 1, 1, 0;\n}\n"
  : "+f"(d[0]),"+f"(d[1]),"+f"(d[2]),"+f"(d[3]),"+f"(d[4]),"+f"(d[5]),"+f"(d[6]),"+f"(d[7]),"+f"(d[8]),"+f"(d[9]),"+f"(d[10]),"+f"(d[11]),"+f"(d[12]),"+f"(d[13]),"+f"(d[14]),"+f"(d[15]),"+f"(d[16]),"+f"(d[17]),"+f"(d[18]),"+f"(d[19]),"+f"(d[20]),"+f"(d[21]),"+f"(d[22]),"+f"(d[23]) : "r"(a0), "r"(a1), "r"(a2), "r"(a3), "l"(db), "r"(sd));
}
template<> __device__ __forceinline__ void wgmma_rs<64,0>(float* d, uint32_t a0, uint32_t a1, uint32_t a2, uint32_t a3, uint64_t db, int sd) {
  asm volatile("{\n.reg .pred p;\nsetp.ne.b32 p, %37, 0;\n"
  "wgmma.mma_async.sync.aligned.m64n64k16.f32.bf16.bf16 {%0,%1,%2,%3,%4,%5,%6,%7,%8,%9,%10,%11,%12,%13,%14,%15,%16,%17,%18,%19,%20,%21,%22,%23,%24,%25,%26,%27,%28,%29,%30,%31}, {%32,%33,%34,%35}, %36, p, 1, 1, 0;\n}\n"
  : "+f"(d[0]),"+f"(d[1]),"+f"(d[2]),"+f"(d[3]),"+f"(d[4]),"+f"(d[5]),"+f"(d[6]),"+f"(d[7]),"+f"(d[8]),"+f"(d[9]),"+f"(d[10]),"+f"(d[11]),"+f"(d[12]),"+f"(d[13]),"+f"(d[14]),"+f"(d[15]),"+f"(d[16]),"+f"(d[17]),"+f"(d[18]),"+f"(d[19]),"+f"(d[20]),"+f"(d[21]),"+f"(d[22]),"+f"(d[23]),"+f"(d[24]),"+f"(d[25]),"+f"(d[26]),"+f"(d[27]),"+f"(d[28]),"+f"(d[29]),"+f"(d[30]),"+f"(d[31]) : "r"(a0), "r"(a1), "r"(a2), "r"(a3), "l"(db), "r"(sd));
}
template<> __device__ __forceinline__ void wgmma_rs<80,0>(float* d, uint32_t a0, uint32_t a1, uint32_t a2, uint32_t a3, uint64_t db, int sd) {
  asm volatile("{\n.reg .pred p;\nsetp.ne.b32 p, %45, 0;\n"
  "wgmma.mma_async.sync.aligned.m64n80k16.f32.bf16.bf16 {%0,%1,%2,%3,%4,%5,%6,%7,%8,%9,%10,%11,%12,%13,%14,%15,%16,%17,%18,%19,%20,%21,%22,%23,%24,%25,%26,%27,%28,%29,%30,%31,%32,%33,%34,%35,%36,%37,%38,%39}, {%40,%41,%42,%43}, %44, p, 1, 1, 0;\n}\n"
  : "+f"(d[0]),"+f"(d[1]),"+f"(d[2]),"+f"(d[3]),"+f"(d[4]),"+f"(d[5]),"+f"(d[6]),"+f"(d[7]),"+f"(d[8]),"+f"(d[9]),"+f"(d[10]),"+f"(d[11]),"+f"(d[12]),"+f"(d[13]),"+f"(d[14]),"+f"(d[15]),"+f"(d[16]),"+f"(d[17]),"+f"(d[18]),"+f"(d[19]),"+f"(d[20]),"+f"(d[21]),"+f"(d[22]),"+f"(d[23]),"+f"(d[24]),"+f"(d[25]),"+f"(d[26]),"+f"(d[27]),"+f"(d[28]),"+f"(d[29]),"+f"(d[30]),"+f"(d[31]),"+f"(d[32]),"+f"(d[33]),"+f"(d[34]),"+f"(d[35]),"+f"(d[36]),"+f"(d[37]),"+f"(d[38]),"+f"(d[39]) : "r"(a0), "r"(a1), "r"(a2), "r"(a3), "l"(db), "r"(sd));
}
template<> __device__ __forceinline__ void wgmma_rs<96,0>(float* d, uint32_t a0, uint32_t a1, uint32_t a2, uint32_t a3, uint64_t db, int sd) {
  asm volatile("{\n.reg .pred p;\nsetp.ne.b32 p, %53, 0;\n"
  "wgmma.mma_async.sync.aligned.m64n96k16.f32.bf16.bf16 {%0,%1,%2,%3,%4,%5,%6,%7,%8,%9,%10,%11,%12,%13,%14,%15,%16,%17,%18,%19,%20,%21,%22,%23,%24,%25,%26,%27,%28,%29,%30,%31,%32,%33,%34,%35,%36,%37,%38,%39,%40,%41,%42,%43,%44,%45,%46,%47}, {%48,%49,%50,%51}, %52, p, 1, 1, 0;\n}\n"
  : "+f"(d[0]),"+f"(d[1]),"+f"(d[2]),"+f"(d[3]),"+f"(d[4]),"+f"(d[5]),"+f"(d[6]),"+f"(d[7]),"+f"(d[8]),"+f"(d[9]),"+f"(d[10]),"+f"(d[11]),"+f"(d[12]),"+f"(d[13]),"+f"(d[14]),"+f"(d[15]),"+f"(d[16]),"+f"(d[17]),"+f"(d[18]),"+f"(d[19]),"+f"(d[20]),"+f"(d[21]),"+f"(d[22]),"+f"(d[23]),"+f"(d[24]),"+f"(d[25]),"+f"(d[26]),"+f"(d[27]),"+f"(d[28]),"+f"(d[29]),"+f"(d[30]),"+f"(d[31]),"+f"(d[32]),"+f"(d[33]),"+f"(d[34]),"+f"(d[35]),"+f"(d[36]),"+f"(d[37]),"+f"(d[38]),"+f"(d[39]),"+f"(d[40]),"+f"(d[41]),"+f"(d[42]),"+f"(d[43]),"+f"(d[44]),"+f"(d[45]),"+f"(d[46]),"+f"(d[47]) : "r"(a0), "r"(a1), "r"(a2), "r"(a3), "l"(db), "r"(sd));
}
template<> __device__ __forceinline__ void wgmma_rs<112,0>(float* d, uint32_t a0, uint32_t a1, uint32_t a2, uint32_t a3, uint64_t db, int sd) {
  asm volatile("{\n.reg .pred p;\nsetp.ne.b32 p, %61, 0;\n"
  "wgmma.mma_async.sync.aligned.m64n112k16.f32.bf16.bf16 {%0,%1,%2,%3,%4,%5,%6,%7,%8,%9,%10,%11,%12,%13,%14,%15,%16,%17,%18,%19,%20,%21,%22,%23,%24,%25,%26,%27,%28,%29,%30,%31,%32,%33,%34,%35,%36,%37,%38,%39,%40,%41,%42,%43,%44,%45,%46,%47,%48,%49,%50,%51,%52,%53,%54,%55}, {%56,%57,%58,%59}, %60, p, 1, 1, 0;\n}\n"
  : "+f"(d[0]),"+f"(d[1]),"+f"(d[2]),"+f"(d[3]),"+f"(d[4]),"+f"(d[5]),"+f"(d[6]),"+f"(d[7]),"+f"(d[8]),"+f"(d[9]),"+f"(d[10]),"+f"(d[11]),"+f"(d[12]),"+f"(d[13]),"+f"(d[14]),"+f"(d[15]),"+f"(d[16]),"+f"(d[17]),"+f"(d[18]),"+f"(d[19]),"+f"(d[20]),"+f"(d[21]),"+f"(d[22]),"+f"(d[23]),"+f"(d[24]),"+f"(d[25]),"+f"(d[26]),"+f"(d[27]),"+f"(d[28]),"+f"(d[29]),"+f"(d[30]),"+f"(d[31]),"+f"(d[32]),"+f"(d[33]),"+f"(d[34]),"+f"(d[35]),"+f"(d[36]),"+f"(d[37]),"+f"(d[38]),"+f"(d[39]),"+f"(d[40]),"+f"(d[41]),"+f"(d[42]),"+f"(d[43]),"+f"(d[44]),"+f"(d[45]),"+f"(d[46]),"+f"(d[47]),"+f"(d[48]),"+f"(d[49]),"+f"(d[50]),"+f"(d[51]),"+f"(d[52]),"+f"(d[53]),"+f"(d[54]),"+f"(d[55]) : "r"(a0), "r"(a1), "r"(a2), "r"(a3), "l"(db), "r"(sd));
}
template<> __device__ __forceinline__ void wgmma_rs<128,0>(float* d, uint32_t a0, uint32_t a1, uint32_t a2, uint32_t a3, uint64_t db, int sd) {
  asm volatile("{\n.reg .pred p;\nsetp.ne.b32 p, %69, 0;\n"
  "wgmma.mma_async.sync.aligned.m64n128k16.f32.bf16.bf16 {%0,%1,%2,%3,%4,%5,%6,%7,%8,%9,%10,%11,%12,%13,%14,%15,%16,%17,%18,%19,%20,%21,%22,%23,%24,%25,%26,%27,%28,%29,%30,%31,%32,%33,%34,%35,%36,%37,%38,%39,%40,%41,%42,%43,%44,%45,%46,%47,%48,%49,%50,%51,%52,%53,%54,%55,%56,%57,%58,%59,%60,%61,%62,%63}, {%64,%65,%66,%67}, %68, p, 1, 1, 0;\n}\n"
  : "+f"(d[0]),"+f"(d[1]),"+f"(d[2]),"+f"(d[3]),"+f"(d[4]),"+f"(d[5]),"+f"(d[6]),"+f"(d[7]),"+f"(d[8]),"+f"(d[9]),"+f"(d[10]),"+f"(d[11]),"+f"(d[12]),"+f"(d[13]),"+f"(d[14]),"+f"(d[15]),"+f"(d[16]),"+f"(d[17]),"+f"(d[18]),"+f"(d[19]),"+f"(d[20]),"+f"(d[21]),"+f"(d[22]),"+f"(d[23]),"+f"(d[24]),"+f"(d[25]),"+f"(d[26]),"+f"(d[27]),"+f"(d[28]),"+f"(d[29]),"+f"(d[30]),"+f"(d[31]),"+f"(d[32]),"+f"(d[33]),"+f"(d[34]),"+f"(d[35]),"+f"(d[36]),"+f"(d[37]),"+f"(d[38]),"+f"(d[39]),"+f"(d[40]),"+f"(d[41]),"+f"(d[42]),"+f"(d[43]),"+f"(d[44]),"+f"(d[45]),"+f"(d[46]),"+f"(d[47]),"+f"(d[48]),"+f"(d[49]),"+f"(d[50]),"+f"(d[51]),"+f"(d[52]),"+f"(d[53]),"+f"(d[54]),"+f"(d[55]),"+f"(d[56]),"+f"(d[57]),"+f"(d[58]),"+f"(d[59]),"+f"(d[60]),"+f"(d[61]),"+f"(d[62]),"+f"(d[63]) : "r"(a0), "r"(a1), "r"(a2), "r"(a3), "l"(db), "r"(sd));
}

namespace {
typedef __nv_bfloat16 bf16;
constexpr int OFF_S    = 1024;
constexpr int STG      = 49152;
constexpr int STG_TX   = 47104;
constexpr int OFF_PHIK = OFF_S - 128;
constexpr int PHIK_HS  = 10240 + 32;
constexpr int OFF_VB   = OFF_S + 49152;
constexpr int OFF_WO   = OFF_S + 75776;
constexpr int OFF_WOT  = OFF_S + 126976;
constexpr int OFF_PHI  = OFF_S + 147456;
constexpr int OFF_KVB  = OFF_PHI + 12800;
constexpr int OFF_U    = OFF_PHI + 40960;
constexpr int OFF_P    = OFF_U + 8960;
constexpr int OFF_KR   = OFF_P + 6144;
constexpr int OFF_KV16 = OFF_P + 16448;
constexpr int OFF_KT   = OFF_P + 17792;
constexpr int OFF_G    = OFF_KT + 12480;
constexpr int SMEM_BYTES = OFF_G + 1024 + 1024;
constexpr int B_FULL = 0, B_EMPTY = 24, B_FULLO = 48, B_EMPTYO = 80, B_WO = 112, B_Y = 120, B_FULLU = 128;
constexpr int C_X = 0, C_Y = 80, C_KV = 88, C_Z = 96, C_G = 104, C_O = 120, C_DONE = 136, C_NUM = 137;

__device__ __align__(1024) unsigned char g_xT[640 * 4096];
__device__ __align__(1024) unsigned char g_y[16 * 640 * 256];
__device__ __align__(1024) unsigned char g_o[16 * 8 * 20480];
__device__ __align__(1024) float g_kv[8 * 4 * 40 * 24];
__device__ __align__(1024) float g_gate[16 * 256];
__device__ __align__(1024) unsigned g_cnt[C_NUM * 32];
#define STAMP(i)
#define STAMPW(i)

constexpr int SPIN_MAX = 1 << 22;
__device__ __forceinline__ uint32_t smem_u32(const void* p) { return (uint32_t)__cvta_generic_to_shared(p); }
__device__ __forceinline__ void mbar_init(uint32_t bar, int cnt) { asm volatile("mbarrier.init.shared::cta.b64 [%0], %1;" ::"r"(bar), "r"(cnt)); }
__device__ __forceinline__ void mbar_expect(uint32_t bar, int bytes) { asm volatile("mbarrier.arrive.expect_tx.shared::cta.b64 _, [%0], %1;" ::"r"(bar), "r"(bytes) : "memory"); }
__device__ __forceinline__ void mbar_arrive(uint32_t bar) { asm volatile("mbarrier.arrive.shared::cta.b64 _, [%0];" ::"r"(bar) : "memory"); }
__device__ __forceinline__ void mbar_arrive_cl(uint32_t bar, uint32_t cta) {
  asm volatile("{\n.reg .b32 ra;\nmapa.shared::cluster.u32 ra, %0, %1;\nmbarrier.arrive.shared::cluster.b64 _, [ra];\n}\n" ::"r"(bar), "r"(cta) : "memory");
}
__device__ __forceinline__ bool mbar_try(uint32_t bar, int parity) {
  uint32_t ok;
  asm volatile("{\n.reg .pred p;\nmbarrier.try_wait.parity.shared::cta.b64 p, [%1], %2;\nselp.u32 %0, 1, 0, p;\n}\n" : "=r"(ok) : "r"(bar), "r"(parity) : "memory");
  return ok;
}
__device__ __forceinline__ void mbar_wait(uint32_t bar, int parity) {
  int n = 0;
  while (!mbar_try(bar, parity)) { if (++n > SPIN_MAX) __trap(); }
}
__device__ __forceinline__ unsigned ld_acq(const unsigned* p) { unsigned v; asm volatile("ld.acquire.gpu.global.u32 %0, [%1];" : "=r"(v) : "l"(p) : "memory"); return v; }
__device__ __forceinline__ void poll(const unsigned* p, unsigned target) {
  int n = 0;
  while ((int)(ld_acq(p) - target) < 0) { if (++n > SPIN_MAX) __trap(); }
}
__device__ __forceinline__ void red_rel(unsigned* p) { asm volatile("red.release.gpu.global.add.u32 [%0], 1;" ::"l"(p) : "memory"); }
__device__ __forceinline__ void red_rlx(unsigned* p) { asm volatile("red.relaxed.gpu.global.add.u32 [%0], 1;" ::"l"(p) : "memory"); }
__device__ __forceinline__ void fence_gpu() { asm volatile("fence.acq_rel.gpu;" ::: "memory"); }
__device__ __forceinline__ void fence_async() { asm volatile("fence.proxy.async.shared::cta;" ::: "memory"); }
__device__ __forceinline__ void fence_async_g() { asm volatile("fence.proxy.async.global;" ::: "memory"); }
__device__ __forceinline__ void bar_sync(int id, int n) { asm volatile("bar.sync %0, %1;" ::"r"(id), "r"(n) : "memory"); }
__device__ __forceinline__ void bar_arrive(int id, int n) { asm volatile("bar.arrive %0, %1;" ::"r"(id), "r"(n) : "memory"); }
__device__ __forceinline__ void wg_fence() { asm volatile("wgmma.fence.sync.aligned;" ::: "memory"); }
__device__ __forceinline__ void wg_commit() { asm volatile("wgmma.commit_group.sync.aligned;" ::: "memory"); }
template <int N> __device__ __forceinline__ void wg_wait() { asm volatile("wgmma.wait_group.sync.aligned %0;" ::"n"(N) : "memory"); }
template <int N> __device__ __forceinline__ void reg_fence(float* d) {
#pragma unroll
  for (int i = 0; i < N; i++) asm volatile("" : "+f"(d[i])::"memory");
}
template <int N> __device__ __forceinline__ void reg_fence(uint32_t* d) {
#pragma unroll
  for (int i = 0; i < N; i++) asm volatile("" : "+r"(d[i])::"memory");
}
__device__ __forceinline__ uint64_t mkdesc(uint32_t addr, uint32_t lbo, uint32_t sbo, uint32_t swz) {
  return (uint64_t)((addr >> 4) & 0x3FFF) | ((uint64_t)(lbo >> 4) << 16) | ((uint64_t)(sbo >> 4) << 32) | ((uint64_t)swz << 62);
}
__device__ __forceinline__ uint32_t pack(float lo, float hi) { uint32_t r; asm("cvt.rn.bf16x2.f32 %0, %1, %2;" : "=r"(r) : "f"(hi), "f"(lo)); return r; }
__device__ __forceinline__ float blo(uint32_t v) { return __uint_as_float(v << 16); }
__device__ __forceinline__ float bhi(uint32_t v) { return __uint_as_float(v & 0xFFFF0000u); }
__device__ __forceinline__ float ex2(float x) { float r; asm("ex2.approx.ftz.f32 %0, %1;" : "=f"(r) : "f"(x)); return r; }
__device__ __forceinline__ float rcp(float x) { float r; asm("rcp.approx.ftz.f32 %0, %1;" : "=f"(r) : "f"(x)); return r; }
__device__ __forceinline__ void sts32(uint32_t a, uint32_t v) { asm volatile("st.shared.u32 [%0], %1;" ::"r"(a), "r"(v) : "memory"); }
__device__ __forceinline__ void sts16(uint32_t a, uint16_t v) { asm volatile("st.shared.u16 [%0], %1;" ::"r"(a), "h"(v) : "memory"); }
__device__ __forceinline__ void sts64f(uint32_t a, float x, float y) { asm volatile("st.shared.v2.f32 [%0], {%1,%2};" ::"r"(a), "f"(x), "f"(y) : "memory"); }
__device__ __forceinline__ void sts128(uint32_t a, uint32_t x, uint32_t y, uint32_t z, uint32_t w) { asm volatile("st.shared.v4.u32 [%0], {%1,%2,%3,%4};" ::"r"(a), "r"(x), "r"(y), "r"(z), "r"(w) : "memory"); }
__device__ __forceinline__ void sts128f(uint32_t a, float x, float y, float z, float w) { asm volatile("st.shared.v4.f32 [%0], {%1,%2,%3,%4};" ::"r"(a), "f"(x), "f"(y), "f"(z), "f"(w) : "memory"); }
__device__ __forceinline__ uint32_t lds32(uint32_t a) { uint32_t v; asm volatile("ld.shared.u32 %0, [%1];" : "=r"(v) : "r"(a) : "memory"); return v; }
__device__ __forceinline__ float lds32f(uint32_t a) { float v; asm volatile("ld.shared.f32 %0, [%1];" : "=f"(v) : "r"(a) : "memory"); return v; }
__device__ __forceinline__ uint32_t lds16(uint32_t a) { uint16_t v; asm volatile("ld.shared.u16 %0, [%1];" : "=h"(v) : "r"(a) : "memory"); return v; }
__device__ __forceinline__ uint4 lds128(uint32_t a) { uint4 v; asm volatile("ld.shared.v4.u32 {%0,%1,%2,%3}, [%4];" : "=r"(v.x), "=r"(v.y), "=r"(v.z), "=r"(v.w) : "r"(a) : "memory"); return v; }
__device__ __forceinline__ float4 lds128f(uint32_t a) { float4 v; asm volatile("ld.shared.v4.f32 {%0,%1,%2,%3}, [%4];" : "=f"(v.x), "=f"(v.y), "=f"(v.z), "=f"(v.w) : "r"(a) : "memory"); return v; }
__device__ __forceinline__ void stsm4(uint32_t a, uint32_t r0, uint32_t r1, uint32_t r2, uint32_t r3) { asm volatile("stmatrix.sync.aligned.m8n8.x4.shared.b16 [%0], {%1,%2,%3,%4};" ::"r"(a), "r"(r0), "r"(r1), "r"(r2), "r"(r3) : "memory"); }
__device__ __forceinline__ void stsm4t(uint32_t a, uint32_t r0, uint32_t r1, uint32_t r2, uint32_t r3) { asm volatile("stmatrix.sync.aligned.m8n8.x4.trans.shared.b16 [%0], {%1,%2,%3,%4};" ::"r"(a), "r"(r0), "r"(r1), "r"(r2), "r"(r3) : "memory"); }
__device__ __forceinline__ uint4 ldsm4(uint32_t a) { uint4 v; asm volatile("ldmatrix.sync.aligned.m8n8.x4.shared.b16 {%0,%1,%2,%3}, [%4];" : "=r"(v.x), "=r"(v.y), "=r"(v.z), "=r"(v.w) : "r"(a) : "memory"); return v; }
__device__ __forceinline__ uint4 ldsm4t(uint32_t a) { uint4 v; asm volatile("ldmatrix.sync.aligned.m8n8.x4.trans.shared.b16 {%0,%1,%2,%3}, [%4];" : "=r"(v.x), "=r"(v.y), "=r"(v.z), "=r"(v.w) : "r"(a) : "memory"); return v; }
__device__ __forceinline__ void mma16816(float* c, uint32_t a0, uint32_t a1, uint32_t a2, uint32_t a3, uint32_t b0, uint32_t b1) {
  asm volatile("mma.sync.aligned.m16n8k16.row.col.f32.bf16.bf16.f32 {%0,%1,%2,%3}, {%4,%5,%6,%7}, {%8,%9}, {%0,%1,%2,%3};"
               : "+f"(c[0]), "+f"(c[1]), "+f"(c[2]), "+f"(c[3]) : "r"(a0), "r"(a1), "r"(a2), "r"(a3), "r"(b0), "r"(b1));
}
__device__ __forceinline__ void tma2d(uint32_t dst, const CUtensorMap* m, int c0, int c1, uint32_t bar) {
  asm volatile("cp.async.bulk.tensor.2d.shared::cluster.global.mbarrier::complete_tx::bytes [%0], [%1, {%3,%4}], [%2];" ::"r"(dst), "l"(m), "r"(bar), "r"(c0), "r"(c1) : "memory");
}
__device__ __forceinline__ void tma3d_mc(uint32_t dst, const CUtensorMap* m, int c0, int c1, int c2, uint32_t bar) {
  asm volatile("cp.async.bulk.tensor.3d.shared::cluster.global.mbarrier::complete_tx::bytes.multicast::cluster [%0], [%1, {%3,%4,%5}], [%2], %6;" ::"r"(dst), "l"(m), "r"(bar), "r"(c0), "r"(c1), "r"(c2), "h"((uint16_t)3) : "memory");
}
__device__ __forceinline__ void tma5d(uint32_t dst, const CUtensorMap* m, int c0, int c1, int c2, int c3, int c4, uint32_t bar) {
  asm volatile("cp.async.bulk.tensor.5d.shared::cluster.global.mbarrier::complete_tx::bytes [%0], [%1, {%3,%4,%5,%6,%7}], [%2];" ::"r"(dst), "l"(m), "r"(bar), "r"(c0), "r"(c1), "r"(c2), "r"(c3), "r"(c4) : "memory");
}
__device__ __forceinline__ void bulk_ld(uint32_t dst, const void* src, int bytes, uint32_t bar) {
  asm volatile("cp.async.bulk.shared::cluster.global.mbarrier::complete_tx::bytes [%0], [%1], %2, [%3];" ::"r"(dst), "l"(src), "r"(bytes), "r"(bar) : "memory");
}
__device__ __forceinline__ void bulk_ld_mc(uint32_t dst, const void* src, int bytes, uint32_t bar) {
  asm volatile("cp.async.bulk.shared::cluster.global.mbarrier::complete_tx::bytes.multicast::cluster [%0], [%1], %2, [%3], %4;" ::"r"(dst), "l"(src), "r"(bytes), "r"(bar), "h"((uint16_t)3) : "memory");
}
__device__ __forceinline__ void tma_st2d(const CUtensorMap* m, uint32_t src, int c0, int c1) {
  asm volatile("cp.async.bulk.tensor.2d.global.shared::cta.bulk_group [%0, {%2,%3}], [%1];" ::"l"(m), "r"(src), "r"(c0), "r"(c1) : "memory");
}
__device__ __forceinline__ void red2(float* p, float a, float b) { asm volatile("red.relaxed.gpu.global.add.v2.f32 [%0], {%1,%2};" ::"l"(p), "f"(a), "f"(b) : "memory"); }
__device__ __forceinline__ float bf2f(uint16_t v) { return __uint_as_float((uint32_t)v << 16); }
__device__ __forceinline__ float rbf(float x) { return __bfloat162float(__float2bfloat16_rn(x)); }

__device__ __forceinline__ void softmax2(const float* p, uint32_t* ph0, uint32_t* ph1) {
  constexpr float L = 1.4426950408889634f;
#pragma unroll
  for (int r = 0; r < 2; r++) {
    uint32_t* ph = r ? ph1 : ph0;
    float mx = fmaxf(p[2 * r], p[2 * r + 1]), mn = fminf(p[2 * r], p[2 * r + 1]);
#pragma unroll
    for (int j = 1; j < 10; j++) {
      mx = fmaxf(mx, fmaxf(p[4 * j + 2 * r], p[4 * j + 2 * r + 1]));
      mn = fminf(mn, fminf(p[4 * j + 2 * r], p[4 * j + 2 * r + 1]));
    }
    const float mxl = -mx * L, mnl = mn * L;
    float e[20], s0 = 0.f, s1 = 0.f;
#pragma unroll
    for (int j = 0; j < 10; j++) {
      e[2 * j] = ex2(fmaf(p[4 * j + 2 * r], L, mxl));
      e[2 * j + 1] = ex2(fmaf(p[4 * j + 2 * r + 1], L, mxl));
      s0 += e[2 * j]; s1 += e[2 * j + 1];
    }
    float rs = rcp(s0 + s1);
#pragma unroll
    for (int j = 0; j < 10; j++) ph[j] = pack(e[2 * j] * rs, e[2 * j + 1] * rs);
    s0 = 0.f; s1 = 0.f;
#pragma unroll
    for (int j = 0; j < 10; j++) {
      e[2 * j] = ex2(fmaf(p[4 * j + 2 * r], -L, mnl));
      e[2 * j + 1] = ex2(fmaf(p[4 * j + 2 * r + 1], -L, mnl));
      s0 += e[2 * j]; s1 += e[2 * j + 1];
    }
    rs = rcp(s0 + s1);
#pragma unroll
    for (int j = 0; j < 10; j++) ph[10 + j] = pack(e[2 * j] * rs, e[2 * j + 1] * rs);
  }
}

struct cf { float x, y; };
__device__ __forceinline__ cf cexpp(float a2, float be, float p) {
  float m = ex2(a2 * p), th = be * p;
  return cf{m * __cosf(th), m * __sinf(th)};
}
__device__ __forceinline__ cf cmul(cf a, cf b) { return cf{fmaf(a.x, b.x, -a.y * b.y), fmaf(a.x, b.y, a.y * b.x)}; }

template <int SH> __device__ __forceinline__ void expand16(uint32_t kv, int base, uint32_t dst) {
  constexpr int NV = (16 >> SH) + 1;
  uint32_t v[NV];
#pragma unroll
  for (int i = 0; i < NV; i++) v[i] = (SH == 0 && i == 0) ? 0u : lds16(kv + 2 * (base + i));
  uint32_t w[8];
#pragma unroll
  for (int i = 0; i < 8; i++) {
    int q[2];
#pragma unroll
    for (int h = 0; h < 2; h++) {
      int e = 16 - (2 * i + h);
      int qq = e >> SH, rem = e & ((1 << SH) - 1), half = (1 << SH) >> 1;
      if (SH > 0 && (rem > half || (rem == half && (qq & 1)))) qq++;
      q[h] = qq;
    }
    w[i] = v[q[0]] | (v[q[1]] << 16);
  }
  sts128(dst, w[0], w[1], w[2], w[3]);
  sts128(dst + 16, w[4], w[5], w[6], w[7]);
}

template <int G> __device__ __forceinline__ void conv_load(uint32_t ka, uint32_t* a) {
#pragma unroll
  for (int h = 0; h < 2; h++) {
    const uint32_t ad = ka - 128 * (2 * G + h);
    uint32_t wm = lds32(ad - 4), w0 = lds32(ad), w1 = lds32(ad + 4);
    a[4 * h + 0] = w0; a[4 * h + 1] = __byte_perm(wm, w0, 0x5432);
    a[4 * h + 2] = w1; a[4 * h + 3] = __byte_perm(w0, w1, 0x5432);
  }
  reg_fence<8>(a);
}
template <int G> struct ConvLoop {
  static __device__ __forceinline__ void run(float* acc, uint32_t ka, uint64_t db, uint32_t* cur, uint32_t* nxt) {
    wg_fence();
    wgmma_rs<128 - 16 * (G / 2), 0>(acc, cur[0], cur[1], cur[2], cur[3], db + 8 * G, 1);
    wgmma_rs<128 - 16 * (G / 2), 0>(acc, cur[4], cur[5], cur[6], cur[7], db + 8 * G + 4, 1);
    wg_commit();
    if (G < 15) {
      wg_wait<1>();
      conv_load<G + 1>(ka, nxt);
      ConvLoop<G + 1>::run(acc, ka, db, nxt, cur);
    }
  }
};
template <> struct ConvLoop<16> { static __device__ __forceinline__ void run(float*, uint32_t, uint64_t, uint32_t*, uint32_t*) {} };

__global__ void __cluster_dims__(2, 1, 1) __launch_bounds__(512, 1)
fused_kernel(const __grid_constant__ CUtensorMap tmX, const __grid_constant__ CUtensorMap tmW, const __grid_constant__ CUtensorMap tmWt,
             const __grid_constant__ CUtensorMap tmWo, const __grid_constant__ CUtensorMap tmOut,
             const uint16_t* __restrict__ wo, const uint32_t* __restrict__ wphi, const uint16_t* __restrict__ lar, const uint16_t* __restrict__ aim,
             const uint16_t* __restrict__ cre, const uint16_t* __restrict__ cim, const uint16_t* __restrict__ ldt,
             const uint16_t* __restrict__ dsk, const uint32_t* __restrict__ gw) {
  extern __shared__ unsigned char smem_raw[];
  const uint32_t sb = (smem_u32(smem_raw) + 1023) & ~1023u;
  const int tid = threadIdx.x, lane = tid & 31;
  const int warp = __shfl_sync(0xffffffffu, tid >> 5, 0);
  const int g = lane >> 2, t = lane & 3;
  const int rank = blockIdx.x & 1, cl = blockIdx.x >> 1;
  const int cg = cl & 7, rt = 2 * (cl >> 3) + rank;
  const int rt3 = 2 * (cl >> 3) + (cg & 1), ct3 = (cg & 6) + rank;

  if (tid == 384) {
    for (int i = 0; i < 3; i++) { mbar_init(sb + B_FULL + 8 * i, 1); mbar_init(sb + B_EMPTY + 8 * i, 17); }
    for (int i = 0; i < 4; i++) { mbar_init(sb + B_FULLO + 8 * i, 1); mbar_init(sb + B_EMPTYO + 8 * i, 16); }
    mbar_init(sb + B_WO, 4); mbar_init(sb + B_Y, 1); mbar_init(sb + B_FULLU, 1); mbar_init(sb + B_FULLU + 8, 1);
    asm volatile("fence.mbarrier_init.release.cluster;" ::: "memory");
    fence_async();
    for (int kb = 0; kb < 3; kb++) {
      mbar_expect(sb + B_FULL + 8 * kb, STG_TX);
      tma2d(sb + OFF_S + ((3 - kb) % 3) * STG, &tmX, 64 * kb, 128 * rt, sb + B_FULL + 8 * kb);
    }
  }
  const unsigned ep1 = (*(volatile unsigned*)&g_cnt[C_DONE * 32] >> 7) + 1;
  asm volatile("barrier.cluster.arrive.release.aligned;\nbarrier.cluster.wait.acquire.aligned;" ::: "memory");

  if (tid == 0) STAMP(64);
  if (warp < 8) {
    asm volatile("setmaxnreg.inc.sync.aligned.u32 176;");
    const int wg = warp >> 2, w = warp & 3;
    {
      uint32_t wv[4];
#pragma unroll
      for (int i = 0; i < 4; i++) { int idx = tid + 256 * i; wv[i] = idx < 800 ? __ldg(wphi + cg * 800 + idx) : 0u; }
#pragma unroll
      for (int i = 0; i < 10; i++) sts128(sb + OFF_PHI + (tid + 256 * i) * 16, 0, 0, 0, 0);
      if (rt == 0) {
        for (int i = tid; i < 960; i += 256) ((float4*)g_kv)[cg * 960 + i] = make_float4(0.f, 0.f, 0.f, 0.f);
      }
      bar_sync(1, 256);
      if (tid == 0) STAMP(65);
      if (rt == 0 && tid == 0) red_rel(&g_cnt[(C_Z + cg) * 32]);
#pragma unroll
      for (int i = 0; i < 4; i++) {
        int idx = tid + 256 * i;
        if (idx < 800) {
          int kk = idx / 10, j = idx - kk * 10, h = kk / 20;
          sts32(sb + OFF_PHI + j * 1280 + kk * 16 + h * 4, wv[i]);
        }
      }
      fence_async();
      bar_sync(1, 256);
    }
    float acc[120];
#pragma unroll
    for (int i = 0; i < 120; i++) acc[i] = 0.f;
    reg_fence<120>(acc);
    STAMPW(0 + warp);
#pragma unroll 1
    for (int kb = 0; kb < 10; kb++) {
      const int s = kb % 3;
      const uint32_t st = sb + OFF_S + ((3 - s) % 3) * STG;
      mbar_wait(sb + B_FULL + 8 * s, (kb / 3) & 1);
      if (warp == 0) STAMPW(40 + kb);
      const uint64_t da = mkdesc(st + wg * 8192, 16, 1024, 1);
      const uint64_t db = mkdesc(st + 16384, 4096, 1024, 1);
      const uint64_t dt = mkdesc(st + 16384 + 12288, 1024, 256, 3);
      wg_fence();
#pragma unroll
      for (int ks = 0; ks < 4; ks++)
      {
        wgmma_ss<192, 0, 1>(acc, da + 2 * ks, db + (ks >> 1) * 1024 + (ks & 1) * 128, 1);
        wgmma_ss<48, 0, 1>(acc + 96, da + 2 * ks, dt + (ks >> 1) * 1024 + (ks & 1) * 32, 1);
      }
      wg_commit();
      wg_wait<0>();
      if (lane < 2) mbar_arrive_cl(sb + B_EMPTY + 8 * s, lane);
    }
    reg_fence<120>(acc);
    STAMPW(8 + warp);
    uint32_t ph0[20], ph1[20];
    float pq[40];
    {
      float pk[40];
      const uint64_t dphi = mkdesc(sb + OFF_PHI, 128, 1280, 0);
      const uint32_t rg = (8 * wg + 2 * w) * 128;
      mbar_wait(sb + B_EMPTY + 16, 0);
      {
        uint32_t va[20];
#pragma unroll
        for (int j = 0; j < 10; j++) {
          const int bv = j < 8 ? 16 + j : 20 + j;
          va[2 * j] = pack(acc[4 * bv], acc[4 * bv + 1]); va[2 * j + 1] = pack(acc[4 * bv + 2], acc[4 * bv + 3]);
        }
        const uint32_t v0 = sb + OFF_VB + rg + (lane & 15) * 16;
        const uint32_t hi = lane >> 4;
        stsm4(v0 + (0 + hi) * 2048, va[0], va[1], va[2], va[3]);
        stsm4(v0 + (3 + hi) * 2048, va[4], va[5], va[6], va[7]);
        stsm4(v0 + (5 + hi) * 2048, va[8], va[9], va[10], va[11]);
        stsm4(v0 + (7 + 2 * hi) * 2048, va[12], va[13], va[14], va[15]);
        stsm4(v0 + (10 + hi) * 2048, va[16], va[17], va[18], va[19]);
        sts128(v0 + (2 + 6 * hi) * 2048, 0x3F803F80u, 0x3F803F80u, 0x3F803F80u, 0x3F803F80u);
      }
      uint32_t fq[20];
#pragma unroll
      for (int j = 0; j < 10; j++) {
        const int bq = j < 8 ? j : 16 + j;
        fq[2 * j] = pack(acc[4 * bq], acc[4 * bq + 1]); fq[2 * j + 1] = pack(acc[4 * bq + 2], acc[4 * bq + 3]);
      }
      uint32_t fa[20];
#pragma unroll
      for (int j = 0; j < 10; j++) {
        const int bk = j < 8 ? 8 + j : 18 + j;
        fa[2 * j] = pack(acc[4 * bk], acc[4 * bk + 1]); fa[2 * j + 1] = pack(acc[4 * bk + 2], acc[4 * bk + 3]);
      }
      reg_fence<20>(fa); reg_fence<20>(fq);
      wg_fence();
#pragma unroll
      for (int s = 0; s < 5; s++) wgmma_rs<80, 1>(pk, fa[4 * s], fa[4 * s + 1], fa[4 * s + 2], fa[4 * s + 3], dphi + 16 * s, s > 0);
      wg_commit();
#pragma unroll
      for (int s = 0; s < 5; s++) wgmma_rs<80, 1>(pq, fq[4 * s], fq[4 * s + 1], fq[4 * s + 2], fq[4 * s + 3], dphi + 16 * s, s > 0);
      wg_commit();
      wg_wait<1>();
      reg_fence<40>(pk);
      if (warp == 0) STAMPW(66);
      softmax2(pk, ph0, ph1);
      mbar_wait(sb + B_EMPTY, 1);
      const uint32_t a0 = sb + OFF_PHIK + t * PHIK_HS + rg + g * 16;
#pragma unroll
      for (int c = 0; c < 5; c++) {
        sts128(a0 + c * 2048, ph0[4 * c], ph0[4 * c + 1], ph0[4 * c + 2], ph0[4 * c + 3]);
        sts128(a0 + c * 2048 + 128, ph1[4 * c], ph1[4 * c + 1], ph1[4 * c + 2], ph1[4 * c + 3]);
      }
    }
    fence_async();
    bar_sync(1, 256);
    STAMPW(16 + warp);
    {
      float kv[32];
      wg_fence();
#pragma unroll
      for (int hh = 0; hh < 2; hh++) {
        const uint64_t da = mkdesc(sb + OFF_PHIK + (2 * wg + hh) * PHIK_HS, 128, 2048, 0);
        const uint64_t db = mkdesc(sb + OFF_VB + (6 * wg + 2 * hh) * 2048, 128, 2048, 0);
#pragma unroll
        for (int s = 0; s < 8; s++) wgmma_ss<32, 1, 1>(kv + 16 * hh, da + 16 * s, db + 16 * s, s > 0);
      }
      wg_commit();
      wg_wait<0>();
      reg_fence<32>(kv);
      reg_fence<40>(pq);
      if (warp == 0) STAMPW(67);
      if (lane < 4) mbar_arrive_cl(sb + B_EMPTYO + 8 * (lane >> 1), lane & 1);
      if (w < 3) {
        float* b0 = g_kv + ((cg * 4 + 2 * wg) * 40 + 16 * w + g) * 24 + 2 * t;
#pragma unroll
        for (int r = 0; r < 2; r++) {
          if (r == 0 || w < 2) {
            float* b = b0 + r * 8 * 24;
            red2(b, kv[2 * r], kv[2 * r + 1]);
            red2(b + 8, kv[4 + 2 * r], kv[5 + 2 * r]);
            if (t < 3) red2(b + 16, t < 2 ? kv[12 + 2 * r] : kv[8 + 2 * r], t < 2 ? kv[13 + 2 * r] : 0.f);
            b += 40 * 24;
            if (t != 1) red2(b, t ? kv[20 + 2 * r] : kv[16 + 2 * r], t ? kv[21 + 2 * r] : 0.f);
            red2(b + 8, kv[24 + 2 * r], kv[25 + 2 * r]);
            red2(b + 16, kv[28 + 2 * r], kv[29 + 2 * r]);
          }
        }
        bar_arrive(2, 224);
      }
    }
    softmax2(pq, ph0, ph1);
    reg_fence<20>(ph0); reg_fence<20>(ph1);
    STAMPW(24 + warp);
    if (lane == 0) poll(&g_cnt[(C_KV + cg) * 32], 16 * ep1);
    __syncwarp();
    if (warp == 0) STAMPW(50);
    {
      float4 f[4];
#pragma unroll
      for (int i = 0; i < 4; i++) { int idx = tid + 256 * i; if (idx < 960) f[i] = __ldcg((const float4*)g_kv + cg * 960 + idx); }
#pragma unroll
      for (int i = 0; i < 4; i++) {
        int idx = tid + 256 * i;
        if (idx < 960) {
          int row = idx / 6, qd = idx - row * 6, h = row / 40, fi = row - h * 40;
          int jn = (h & 1) ? (qd == 0 ? 10 : 2 * qd - 2) : 2 * qd;
          uint32_t a = sb + OFF_KVB + jn * 2560 + (fi >> 1) * 128 + (2 * h + (fi & 1)) * 16 + 4 * h;
          sts32(a, pack(f[i].x, f[i].y));
          if (jn < 10) sts32(a + 2560, pack(f[i].z, f[i].w));
        }
      }
    }
    fence_async();
    bar_sync(1, 256);
    {
      float p[44];
      if (warp == 0) STAMPW(68);
      const uint64_t db = mkdesc(sb + OFF_KVB, 128, 2560, 0);
      wg_fence();
#pragma unroll
      for (int s = 0; s < 10; s++) wgmma_rs<88, 1>(p, ph0[2 * s], ph1[2 * s], ph0[2 * s + 1], ph1[2 * s + 1], db + 16 * s, s > 0);
      wg_commit();
      wg_wait<0>();
      reg_fence<44>(p);
      if (warp == 0) STAMPW(69);
      if (lane < 4) mbar_arrive_cl(sb + B_EMPTYO + 16 + 8 * (lane >> 1), lane & 1);
      const float r0 = rcp(p[40] + 1e-6f), r1 = rcp(p[42] + 1e-6f);
      uint32_t* o = (uint32_t*)(g_o + (rt * 8 + cg) * 20480 + (8 * wg + 2 * w) * 128) + lane;
#pragma unroll
      for (int j = 0; j < 10; j++) {
        __stcg(o + j * 512, pack(p[4 * j] * r0, p[4 * j + 1] * r0));
        __stcg(o + j * 512 + 32, pack(p[4 * j + 2] * r1, p[4 * j + 3] * r1));
      }
      __syncwarp();
      if (lane == 0) red_rel(&g_cnt[(C_O + rt) * 32 + cg]);
    }
    if (warp == 0) STAMPW(51);
    float p[40];
#pragma unroll
    for (int i = 0; i < 40; i++) p[i] = 0.f;
    reg_fence<40>(p);
    mbar_wait(sb + B_WO, 0);
#pragma unroll 1
    for (int i = 0; i < 8; i++) {
      const int st = i & 3;
      const uint32_t oa = sb + (st < 2 ? OFF_S : OFF_PHI) + (st & 1) * 20480 + wg * 1024;
      const uint32_t wa = OFF_WO + (((i + 3) & 7) - 3) * 10240;
      const uint32_t ta = OFF_WOT + (i >> 2) * 10240 + (i & 3) * 32;
      const uint64_t da = mkdesc(oa, 2048, 128, 0);
      const uint64_t db = mkdesc(sb + wa, ta - wa, 1024, 1);
      mbar_wait(sb + B_FULLO + 8 * st, i >> 2);
      if (warp == 0) STAMPW(52 + i);
      wg_fence();
#pragma unroll
      for (int ks = 0; ks < 5; ks++) wgmma_ss<80, 0, 1>(p, da + 256 * ks, db + 128 * ks, 1);
      wg_commit();
      wg_wait<0>();
      if (i < 6 && lane < 2) mbar_arrive_cl(sb + B_EMPTYO + 8 * st, lane);
    }
    reg_fence<40>(p);
    if (warp == 0) STAMPW(60);
    mbar_wait(sb + B_Y, 0);
    mbar_wait(sb + B_EMPTYO + 8, 0);
    if (warp == 0) STAMPW(61);
    {
      const int r0 = 64 * wg + 16 * w + g;
      const float l0 = lds32f(sb + OFF_G + r0 * 4) + lds32f(sb + OFF_G + 512 + r0 * 4);
      const float l1 = lds32f(sb + OFF_G + r0 * 4 + 32) + lds32f(sb + OFF_G + 512 + r0 * 4 + 32);
      const float g0 = rcp(1.f + ex2(-1.4426950408889634f * l0)), g1 = rcp(1.f + ex2(-1.4426950408889634f * l1));
      const uint32_t ya = sb + OFF_S + ((lane >> 4) * 8 + (lane & 7)) * 256 + (((8 * wg + 2 * w + ((lane >> 3) & 1)) ^ (lane & 7)) * 16);
      const uint32_t ob = sb + OFF_S + 20480 + warp * 2560;
      const uint32_t oa = ob + (lane & 15) * 160 + (lane >> 4) * 16;
#pragma unroll
      for (int j = 0; j < 5; j++) {
        const uint4 y = ldsm4t(ya + j * 4096);
        const float* a = p + 8 * j;
        uint32_t o0 = pack(fmaf(g0, a[0] - blo(y.x), blo(y.x)), fmaf(g0, a[1] - bhi(y.x), bhi(y.x)));
        uint32_t o1 = pack(fmaf(g1, a[2] - blo(y.y), blo(y.y)), fmaf(g1, a[3] - bhi(y.y), bhi(y.y)));
        uint32_t o2 = pack(fmaf(g0, a[4] - blo(y.z), blo(y.z)), fmaf(g0, a[5] - bhi(y.z), bhi(y.z)));
        uint32_t o3 = pack(fmaf(g1, a[6] - blo(y.w), blo(y.w)), fmaf(g1, a[7] - bhi(y.w), bhi(y.w)));
        stsm4(oa + j * 32, o0, o1, o2, o3);
      }
      fence_async();
      __syncwarp();
      if (lane == 0) {
        tma_st2d(&tmOut, ob, 80 * ct3, 128 * rt3 + 16 * warp);
        asm volatile("cp.async.bulk.commit_group;\ncp.async.bulk.wait_group.read 0;" ::: "memory");
      }
    }
    STAMPW(32 + warp);
  } else if (warp < 12) {
    asm volatile("setmaxnreg.dec.sync.aligned.u32 112;");
    const int w = warp & 3, th = tid & 127;
    const int cta = blockIdx.x;
    uint16_t n_lar, n_aim, n_cre, n_cim, n_ldt, n_dsk;
    {
      const int i = cta * 128 + th;
      n_lar = __ldg(lar + i); n_aim = __ldg(aim + i); n_cre = __ldg(cre + i); n_cim = __ldg(cim + i);
      n_ldt = __ldg(ldt + cta); n_dsk = __ldg(dsk + cta);
    }
    if (th < 64 && (th & 15) < 12) sts128(sb + OFF_U + (th >> 4) * 2240 + 2048 + (th & 15) * 16, 0, 0, 0, 0);
    fence_async();
#pragma unroll 1
    for (int it = 0; it < 8; it++) {
      if (it >= 3) {
        const int j = it - 3, ch = 128 * j + cta;
        bar_sync(4, 128);
        const uint32_t ka = sb + OFF_KT + (j % 3) * 4160 + 2 * (2064 - 16 * w - 2 * g + 4 * t);
        float acc[64];
        uint32_t a0[8], a1[8];
#pragma unroll
        for (int i = 0; i < 64; i++) acc[i] = 0.f;
        reg_fence<64>(acc);
        conv_load<0>(ka, a0);
        mbar_wait(sb + B_FULLU + 8 * (j & 1), (j >> 1) & 1);
        if (w == 0) STAMPW(70 + j);
        ConvLoop<0>::run(acc, ka, mkdesc(sb + OFF_U + (j & 1) * 4480, 2240, 128, 0), a0, a1);
        wg_wait<0>();
        reg_fence<64>(acc);
        if (w == 0) STAMPW(75 + j);
        {
          const uint32_t pa = sb + OFF_P + w * 4096 + ((lane >> 3) & 1) * 2048 + ((lane >> 4) * 8 + (lane & 7)) * 16;
#pragma unroll
          for (int i = 0; i < 8; i++) {
            const float* a = acc + 8 * i;
            stsm4t(pa + i * 256, pack(a[0], a[1]), pack(a[2], a[3]), pack(a[4], a[5]), pack(a[6], a[7]));
          }
        }
        bar_sync(4, 128);
        {
          float s[16];
#pragma unroll
          for (int i = 0; i < 16; i++) s[i] = 0.f;
#pragma unroll
          for (int ww = 0; ww < 4; ww++) {
            if (th >= ww) {
              const uint32_t pa = sb + OFF_P + ww * 4096 + (127 - th + ww) * 16;
              const uint4 e = lds128(pa), o = lds128(pa + 2048);
              s[0] += blo(e.x); s[2] += bhi(e.x); s[4] += blo(e.y); s[6] += bhi(e.y);
              s[8] += blo(e.z); s[10] += bhi(e.z); s[12] += blo(e.w); s[14] += bhi(e.w);
              s[1] += blo(o.x); s[3] += bhi(o.x); s[5] += blo(o.y); s[7] += bhi(o.y);
              s[9] += blo(o.z); s[11] += bhi(o.z); s[13] += blo(o.w); s[15] += bhi(o.w);
            }
          }
          unsigned char* yb = g_y + ((th >> 3) * 640 + ch) * 256;
          const int c0 = 2 * (th & 7), sw = ch & 7;
          __stcg((uint4*)(yb + ((c0 ^ sw) * 16)), make_uint4(pack(s[0], s[1]), pack(s[2], s[3]), pack(s[4], s[5]), pack(s[6], s[7])));
          __stcg((uint4*)(yb + (((c0 + 1) ^ sw) * 16)), make_uint4(pack(s[8], s[9]), pack(s[10], s[11]), pack(s[12], s[13]), pack(s[14], s[15])));
        }
        bar_arrive(5 + (j & 1), 160);
        if (w == 0) STAMPW(80 + j);
      }
      if (it < 5) {
        bar_sync(4, 128);
        const float dt = rbf(expf(bf2f(n_ldt)));
        const float al = -rbf(expf(bf2f(n_lar))) * dt, be = bf2f(n_aim) * dt;
        const cf c{2.f * (bf2f(n_cre) * dt), 2.f * (bf2f(n_cim) * dt)};
        const float dskip = bf2f(n_dsk);
        if (it < 4) {
          const int ch = 128 * (it + 1) + cta, i = ch * 128 + th;
          n_lar = __ldg(lar + i); n_aim = __ldg(aim + i); n_cre = __ldg(cre + i); n_cim = __ldg(cim + i);
          n_ldt = __ldg(ldt + ch); n_dsk = __ldg(dsk + ch);
        }
        const float a2 = al * 1.4426950408889634f;
        {
          const cf z1 = cexpp(a2, be, 1.f), z128 = cexpp(a2, be, 128.f), z256 = cexpp(a2, be, 256.f), ze = cexpp(a2, be, 2048.f);
          const uint32_t ca = sb + OFF_P + th * 48;
          sts128f(ca, a2, be, c.x, c.y);
          sts128f(ca + 16, z1.x, z1.y, z128.x, z128.y);
          sts64f(ca + 32, z256.x, z256.y);
          float e = fmaf(c.x, ze.x, -c.y * ze.y);
#pragma unroll
          for (int o = 16; o; o >>= 1) e += __shfl_xor_sync(0xffffffffu, e, o);
          if (lane == 0) sts32(sb + OFF_KR + (w * 644 + 640) * 4, __float_as_uint(e));
        }
        __syncwarp();
        float kc[20];
#pragma unroll
        for (int i = 0; i < 20; i++) kc[i] = 0.f;
        const float pA = 16.f * g, pB = 2.f * g, p3 = 512.f + 256.f * (g >> 2) + 4.f * (g & 3), p4 = 1024.f + 256.f * (g >> 1) + 8.f * (g & 1);
#pragma unroll 1
        for (int ks = 0; ks < 4; ks++) {
          uint32_t fa[4], fb[5][2];
#pragma unroll
          for (int h = 0; h < 2; h++) {
            const uint32_t ca = sb + OFF_P + (32 * w + 8 * ks + 4 * h + t) * 48;
            const float4 c0 = lds128f(ca), c1 = lds128f(ca + 16), c2 = lds128f(ca + 32);
            const cf A0 = cmul(cexpp(c0.x, c0.y, pA), cf{c0.z, c0.w});
            const cf A1 = cmul(A0, cf{c1.z, c1.w});
            const cf B0 = cexpp(c0.x, c0.y, pB), B1 = cmul(B0, cf{c1.x, c1.y}), B2 = cmul(B0, cf{c2.x, c2.y});
            const cf B3 = cexpp(c0.x, c0.y, p3), B4 = cexpp(c0.x, c0.y, p4);
            fa[2 * h] = pack(A0.x, -A0.y); fa[2 * h + 1] = pack(A1.x, -A1.y);
            fb[0][h] = pack(B0.x, B0.y); fb[1][h] = pack(B1.x, B1.y); fb[2][h] = pack(B2.x, B2.y);
            fb[3][h] = pack(B3.x, B3.y); fb[4][h] = pack(B4.x, B4.y);
          }
#pragma unroll
          for (int q = 0; q < 5; q++) mma16816(kc + 4 * q, fa[0], fa[1], fa[2], fa[3], fb[q][0], fb[q][1]);
        }
        {
          const uint32_t ra = sb + OFF_KR + w * 644 * 4;
#pragma unroll
          for (int r = 0; r < 2; r++) {
            const int i = g + 8 * r;
            sts128f(ra + (16 * i + 4 * t) * 4, kc[2 * r], kc[4 + 2 * r], kc[1 + 2 * r], kc[5 + 2 * r]);
            sts64f(ra + (256 + 8 * i + 2 * t) * 4, kc[8 + 2 * r], kc[9 + 2 * r]);
            sts64f(ra + (384 + 64 * (t >> 1) + 4 * i + 2 * (t & 1)) * 4, kc[12 + 2 * r], kc[13 + 2 * r]);
            sts64f(ra + (512 + 32 * t + 2 * i) * 4, kc[16 + 2 * r], kc[17 + 2 * r]);
          }
        }
        bar_sync(4, 128);
#pragma unroll
        for (int i = 0; i < 6; i++) {
          const int idx = th + 128 * i;
          if (i < 5 || th == 0) {
            const uint32_t ra = sb + OFF_KR + idx * 4;
            float v = (lds32f(ra) + lds32f(ra + 2576)) + (lds32f(ra + 5152) + lds32f(ra + 7728));
            if (idx == 0) v += dskip;
            sts16(sb + OFF_KV16 + idx * 2, (uint16_t)(pack(v, 0.f) & 0xFFFF));
          }
        }
        bar_sync(4, 128);
        {
          const uint32_t kt = sb + OFF_KT + (it % 3) * 4160, kv = sb + OFF_KV16;
          const uint32_t dst = kt + 2 * (2064 - 16 * th - 16);
          if (th >= 64) expand16<3>(kv, 512 + 2 * (th - 64), dst);
          else if (th >= 32) expand16<2>(kv, 384 + 4 * (th - 32), dst);
          else if (th >= 16) expand16<1>(kv, 256 + 8 * (th - 16), dst);
          else expand16<0>(kv, 16 * th, dst);
          if (th == 127) {
            sts128(kt + 2 * 2064, lds16(kv), 0, 0, 0);
            sts128(kt + 2 * 2064 + 16, 0, 0, 0, 0);
          }
        }
        if (w == 0) STAMPW(85 + it);
      }
    }
  } else {
    asm volatile("setmaxnreg.dec.sync.aligned.u32 48;");
    if (warp == 12) {
      if (lane == 0) {
#pragma unroll 1
        for (int kb = 0; kb < 10; kb++) {
          const int s = kb % 3;
          const uint32_t st = sb + OFF_S + ((3 - s) % 3) * STG, bar = sb + B_FULL + 8 * s;
          if (kb == 5) poll(&g_cnt[(C_Z + cg) * 32], ep1);
          if (kb >= 3) {
            mbar_wait(sb + B_EMPTY + 8 * s, (kb / 3 - 1) & 1);
            mbar_expect(bar, STG_TX);
            tma2d(st, &tmX, 64 * kb, 128 * rt, bar);
          }
          tma3d_mc(st + 16384 + rank * 16384, &tmW, 80 * cg, 64 * kb + 32 * rank, 0, bar);
          tma3d_mc(st + 16384 + rank * 16384 + 12288, &tmWt, 80 * cg + 64, 64 * kb + 32 * rank, 0, bar);
        }
        const uint32_t wb = sb + B_WO;
        mbar_wait(sb + B_EMPTY + 8, 0);
        mbar_expect(wb, 20480);
        for (int u = 3; u < 5; u++) tma5d(sb + OFF_WO + u * 10240, &tmWo, 80 * ct3, 0, 0, 0, u, wb);
        mbar_wait(sb + B_EMPTY + 16, 0);
        mbar_expect(wb, 30720);
        for (int u = 0; u < 3; u++) tma5d(sb + OFF_WO + u * 10240, &tmWo, 80 * ct3, 0, 0, 0, u, wb);
        mbar_wait(sb + B_EMPTYO, 0);
        mbar_expect(wb, 30720);
        for (int u = 5; u < 8; u++) tma5d(sb + OFF_WO + (u - 8) * 10240, &tmWo, 80 * ct3, 0, 0, 0, u, wb);
      }
      __syncwarp();
      {
        unsigned ready = 0;
        int next = 0, n = 0;
        while (next < 8) {
          bool ok = false;
          if (lane < 8 && !((ready >> lane) & 1)) ok = (int)(ld_acq(&g_cnt[(C_O + rt3) * 32 + lane]) - 8 * ep1) >= 0;
          ready |= __ballot_sync(0xffffffffu, ok);
          while (next < 8 && ((ready >> next) & 1)) {
            if (lane == next) {
              const int st = next & 3;
              const uint32_t oa = sb + (st < 2 ? OFF_S : OFF_PHI) + (st & 1) * 20480;
              mbar_wait(sb + B_EMPTYO + 8 * st, next >> 2);
              fence_async_g();
              mbar_expect(sb + B_FULLO + 8 * st, 20480);
              bulk_ld_mc(oa + rank * 10240, g_o + (rt3 * 8 + next) * 20480 + rank * 10240, 10240, sb + B_FULLO + 8 * st);
            }
            __syncwarp();
            next++;
          }
          if (++n > SPIN_MAX) __trap();
        }
      }
      if (lane == 0) {
        poll(&g_cnt[(C_G + rt3) * 32], 16 * ep1);
        poll(&g_cnt[(C_Y + ct3) * 32], 80 * ep1);
        mbar_wait(sb + B_EMPTYO, 0);
        fence_async_g();
        mbar_expect(sb + B_Y, 20480 + 1024);
        bulk_ld(sb + OFF_S, g_y + (rt3 * 640 + 80 * ct3) * 256, 20480, sb + B_Y);
        bulk_ld(sb + OFF_G, g_gate + rt3 * 256, 1024, sb + B_Y);
      }
    } else if (warp == 14) {
      const int cta = blockIdx.x;
#pragma unroll 1
      for (int j = 0; j < 7; j++) {
        if (j >= 2) {
          bar_sync(5 + (j & 1), 160);
          if (lane == 0) red_rel(&g_cnt[(C_Y + (128 * (j - 2) + cta) / 80) * 32]);
        }
        if (j < 5 && lane == 0) {
          poll(&g_cnt[(C_X + (2 * j + (cta >> 6)) * 8 + ((cta & 63) >> 3)) * 32], 16 * ep1);
          fence_async_g();
          const uint32_t bar = sb + B_FULLU + 8 * (j & 1), ub = sb + OFF_U + (j & 1) * 4480;
          const unsigned char* src = g_xT + (128 * j + cta) * 4096;
          mbar_expect(bar, 4096);
          bulk_ld(ub, src, 2048, bar);
          bulk_ld(ub + 2240, src + 2048, 2048, bar);
        }
        __syncwarp();
      }
    } else {
      const int par = (warp - 13) >> 1;
      float ga[4] = {0.f, 0.f, 0.f, 0.f};
      const int trow = 16 * ((lane & 7) >> 1) + 4 * (lane >> 3) + (lane & 1);
      const int grow = 16 * cg + (lane & 15);
#pragma unroll 1
      for (int kb = par; kb < 10; kb += 2) {
        const int s = kb % 3;
        const uint32_t st = sb + OFF_S + ((3 - s) % 3) * STG;
        uint32_t gb[8];
#pragma unroll
        for (int i = 0; i < 8; i++) gb[i] = __ldg(gw + 32 * kb + 4 * i + t);
        if (kb >= 3) mbar_wait(sb + B_EMPTY + 8 * s, (kb / 3 - 1) & 1);
        mbar_wait(sb + B_FULL + 8 * s, (kb / 3) & 1);
#pragma unroll
        for (int ks = 0; ks < 4; ks++) {
          const uint4 a = ldsm4(st + grow * 128 + (((2 * ks + (lane >> 4)) ^ (grow & 7)) * 16));
          mma16816(ga, a.x, a.y, a.z, a.w, gb[2 * ks], gb[2 * ks + 1]);
        }
        uint4 v[4];
#pragma unroll
        for (int i = 0; i < 4; i++) {
          const int r = trow + 64 * (i & 1) + 2 * (i >> 1);
          v[i] = ldsm4t(st + r * 128 + ((cg ^ (r & 7)) * 16));
        }
        unsigned char* dst = g_xT + (64 * kb + 8 * cg + g) * 4096 + (127 - 8 * rt - t) * 16;
#pragma unroll
        for (int i = 0; i < 4; i++) __stcg((uint4*)(dst + (i >> 1) * 2048 - (i & 1) * 64), v[i]);
        if (kb >= 8 && t == 0) {
          float* gp = g_gate + rt * 256 + par * 128 + 16 * cg + g;
          __stcg(gp, ga[0]); __stcg(gp + 8, ga[2]);
        }
        __syncwarp();
        if (lane == 0) {
          mbar_arrive(sb + B_EMPTY + 8 * s);
          fence_gpu();
          red_rlx(&g_cnt[(C_X + kb * 8 + cg) * 32]);
          if (kb >= 8) red_rlx(&g_cnt[(C_G + rt) * 32]);
        }
      }
      if (par == 0) {
        mbar_wait(sb + B_EMPTY + 8, 0);
        const int c = lane & 1, rr = lane >> 1;
#pragma unroll 1
        for (int i = 0; i < 40; i++) {
          const int ch = i / 5, rho = (i - ch * 5) * 16 + rr;
          const int row = 80 * ch + 20 * ((rho >> 1) & 3) + 2 * (rho >> 3) + (rho & 1);
          const uint32_t dst = sb + OFF_WOT + (ch >> 2) * 10240 + rho * 128 + (((2 * (ch & 3) + c) ^ (rho & 7)) * 16);
          asm volatile("cp.async.cg.shared.global [%0], [%1], 16;" ::"r"(dst), "l"(wo + row * 640 + 80 * ct3 + 64 + 8 * c) : "memory");
        }
        asm volatile("cp.async.wait_all;" ::: "memory");
        fence_async();
        __syncwarp();
        if (lane == 0) mbar_arrive(sb + B_WO);
        bar_sync(2, 224);
        STAMPW(90);
        if (lane == 0) red_rel(&g_cnt[(C_KV + cg) * 32]);
        STAMPW(91);
      }
    }
  }
  __syncwarp();
  asm volatile("barrier.cluster.arrive.release.aligned;\nbarrier.cluster.wait.acquire.aligned;" ::: "memory");
  if (tid == 0) red_rlx(&g_cnt[C_DONE * 32]);
}

typedef CUresult (*EncFn)(CUtensorMap*, CUtensorMapDataType, cuuint32_t, void*, const cuuint64_t*, const cuuint64_t*, const cuuint32_t*,
                          const cuuint32_t*, CUtensorMapInterleave, CUtensorMapSwizzle, CUtensorMapL2promotion, CUtensorMapFloatOOBfill);
int enc(EncFn fn, CUtensorMap* m, void* p, int rank, const cuuint64_t* gd, const cuuint64_t* gs, const cuuint32_t* bd, CUtensorMapSwizzle sw) {
  const cuuint32_t es[5] = {1, 1, 1, 1, 1};
  return (int)fn(m, CU_TENSOR_MAP_DATA_TYPE_BFLOAT16, rank, p, gd, gs, bd, es, CU_TENSOR_MAP_INTERLEAVE_NONE, sw,
                 CU_TENSOR_MAP_L2_PROMOTION_L2_128B, CU_TENSOR_MAP_FLOAT_OOB_FILL_NONE);
}
int g_enc_err = 0;
}

extern "C" void kernel_launch(void* const* d_in, const int* in_sizes, int n_in, void* d_out, int out_size) {
  static EncFn fn = nullptr;
  if (!fn) {
    void* p = nullptr;
    cudaDriverEntryPointQueryResult qr;
    cudaGetDriverEntryPoint("cuTensorMapEncodeTiled", &p, cudaEnableDefault, &qr);
    fn = (EncFn)p;
    cudaFuncSetAttribute(fused_kernel, cudaFuncAttributeMaxDynamicSharedMemorySize, SMEM_BYTES);
  }
  CUtensorMap mX, mW, mWt, mWo, mOut;
  int e = 0;
  { cuuint64_t gd[2] = {640, 2048}, gs[1] = {1280}; cuuint32_t bd[2] = {64, 128}; e |= enc(fn, &mX, d_in[0], 2, gd, gs, bd, CU_TENSOR_MAP_SWIZZLE_128B); }
  { cuuint64_t gd[3] = {640, 640, 3}, gs[2] = {3840, 1280}; cuuint32_t bd[3] = {64, 32, 3}; e |= enc(fn, &mW, d_in[1], 3, gd, gs, bd, CU_TENSOR_MAP_SWIZZLE_128B) << 4; }
  { cuuint64_t gd[3] = {640, 640, 3}, gs[2] = {3840, 1280}; cuuint32_t bd[3] = {16, 32, 3}; e |= enc(fn, &mWt, d_in[1], 3, gd, gs, bd, CU_TENSOR_MAP_SWIZZLE_32B) << 8; }
  { cuuint64_t gd[5] = {640, 2, 4, 10, 8}, gs[4] = {1280, 25600, 2560, 102400}; cuuint32_t bd[5] = {64, 2, 4, 10, 1}; e |= enc(fn, &mWo, d_in[3], 5, gd, gs, bd, CU_TENSOR_MAP_SWIZZLE_128B) << 12; }
  { cuuint64_t gd[2] = {640, 2048}, gs[1] = {1280}; cuuint32_t bd[2] = {80, 16}; e |= enc(fn, &mOut, d_out, 2, gd, gs, bd, CU_TENSOR_MAP_SWIZZLE_NONE) << 20; }
  g_enc_err = e;
  if (e) return;
  fused_kernel<<<128, 512, SMEM_BYTES, cudaStreamPerThread>>>(mX, mW, mWt, mWo, mOut, (const uint16_t*)d_in[3], (const uint32_t*)d_in[2], (const uint16_t*)d_in[5],
      (const uint16_t*)d_in[6], (const uint16_t*)d_in[7], (const uint16_t*)d_in[8], (const uint16_t*)d_in[9], (const uint16_t*)d_in[10],
      (const uint32_t*)d_in[11]);
}
```

```cpp
#include <cuda_runtime.h>
#include <cuda_bf16.h>
#include <cuda.h>
#include <stdint.h>

template<int N, int TA, int TB> __device__ __forceinline__ void wgmma_ss(float* d, uint64_t da, uint64_t db, int sd);
template<int N, int TB> __device__ __forceinline__ void wgmma_rs(float* d, uint32_t a0, uint32_t a1, uint32_t a2, uint32_t a3, uint64_t db, int sd);
template<> __device__ __forceinline__ void wgmma_ss<192,0,1>(float* d, uint64_t da, uint64_t db, int sd) {
  asm volatile("{\n.reg .pred p;\nsetp.ne.b32 p, %98, 0;\n"
  "wgmma.mma_async.sync.aligned.m64n192k16.f32.bf16.bf16 {%0,%1,%2,%3,%4,%5,%6,%7,%8,%9,%10,%11,%12,%13,%14,%15,%16,%17,%18,%19,%20,%21,%22,%23,%24,%25,%26,%27,%28,%29,%30,%31,%32,%33,%34,%35,%36,%37,%38,%39,%40,%41,%42,%43,%44,%45,%46,%47,%48,%49,%50,%51,%52,%53,%54,%55,%56,%57,%58,%59,%60,%61,%62,%63,%64,%65,%66,%67,%68,%69,%70,%71,%72,%73,%74,%75,%76,%77,%78,%79,%80,%81,%82,%83,%84,%85,%86,%87,%88,%89,%90,%91,%92,%93,%94,%95}, %96, %97, p, 1, 1, 0, 1;\n}\n"
  : "+f"(d[0]),"+f"(d[1]),"+f"(d[2]),"+f"(d[3]),"+f"(d[4]),"+f"(d[5]),"+f"(d[6]),"+f"(d[7]),"+f"(d[8]),"+f"(d[9]),"+f"(d[10]),"+f"(d[11]),"+f"(d[12]),"+f"(d[13]),"+f"(d[14]),"+f"(d[15]),"+f"(d[16]),"+f"(d[17]),"+f"(d[18]),"+f"(d[19]),"+f"(d[20]),"+f"(d[21]),"+f"(d[22]),"+f"(d[23]),"+f"(d[24]),"+f"(d[25]),"+f"(d[26]),"+f"(d[27]),"+f"(d[28]),"+f"(d[29]),"+f"(d[30]),"+f"(d[31]),"+f"(d[32]),"+f"(d[33]),"+f"(d[34]),"+f"(d[35]),"+f"(d[36]),"+f"(d[37]),"+f"(d[38]),"+f"(d[39]),"+f"(d[40]),"+f"(d[41]),"+f"(d[42]),"+f"(d[43]),"+f"(d[44]),"+f"(d[45]),"+f"(d[46]),"+f"(d[47]),"+f"(d[48]),"+f"(d[49]),"+f"(d[50]),"+f"(d[51]),"+f"(d[52]),"+f"(d[53]),"+f"(d[54]),"+f"(d[55]),"+f"(d[56]),"+f"(d[57]),"+f"(d[58]),"+f"(d[59]),"+f"(d[60]),"+f"(d[61]),"+f"(d[62]),"+f"(d[63]),"+f"(d[64]),"+f"(d[65]),"+f"(d[66]),"+f"(d[67]),"+f"(d[68]),"+f"(d[69]),"+f"(d[70]),"+f"(d[71]),"+f"(d[72]),"+f"(d[73]),"+f"(d[74]),"+f"(d[75]),"+f"(d[76]),"+f"(d[77]),"+f"(d[78]),"+f"(d[79]),"+f"(d[80]),"+f"(d[81]),"+f"(d[82]),"+f"(d[83]),"+f"(d[84]),"+f"(d[85]),"+f"(d[86]),"+f"(d[87]),"+f"(d[88]),"+f"(d[89]),"+f"(d[90]),"+f"(d[91]),"+f"(d[92]),"+f"(d[93]),"+f"(d[94]),"+f"(d[95]) : "l"(da), "l"(db), "r"(sd));
}
template<> __device__ __forceinline__ void wgmma_ss<48,0,1>(float* d, uint64_t da, uint64_t db, int sd) {
  asm volatile("{\n.reg .pred p;\nsetp.ne.b32 p, %26, 0;\n"
  "wgmma.mma_async.sync.aligned.m64n48k16.f32.bf16.bf16 {%0,%1,%2,%3,%4,%5,%6,%7,%8,%9,%10,%11,%12,%13,%14,%15,%16,%17,%18,%19,%20,%21,%22,%23}, %24, %25, p, 1, 1, 0, 1;\n}\n"
  : "+f"(d[0]),"+f"(d[1]),"+f"(d[2]),"+f"(d[3]),"+f"(d[4]),"+f"(d[5]),"+f"(d[6]),"+f"(d[7]),"+f"(d[8]),"+f"(d[9]),"+f"(d[10]),"+f"(d[11]),"+f"(d[12]),"+f"(d[13]),"+f"(d[14]),"+f"(d[15]),"+f"(d[16]),"+f"(d[17]),"+f"(d[18]),"+f"(d[19]),"+f"(d[20]),"+f"(d[21]),"+f"(d[22]),"+f"(d[23]) : "l"(da), "l"(db), "r"(sd));
}
template<> __device__ __forceinline__ void wgmma_ss<48,1,1>(float* d, uint64_t da, uint64_t db, int sd) {
  asm volatile("{\n.reg .pred p;\nsetp.ne.b32 p, %26, 0;\n"
  "wgmma.mma_async.sync.aligned.m64n48k16.f32.bf16.bf16 {%0,%1,%2,%3,%4,%5,%6,%7,%8,%9,%10,%11,%12,%13,%14,%15,%16,%17,%18,%19,%20,%21,%22,%23}, %24, %25, p, 1, 1, 1, 1;\n}\n"
  : "+f"(d[0]),"+f"(d[1]),"+f"(d[2]),"+f"(d[3]),"+f"(d[4]),"+f"(d[5]),"+f"(d[6]),"+f"(d[7]),"+f"(d[8]),"+f"(d[9]),"+f"(d[10]),"+f"(d[11]),"+f"(d[12]),"+f"(d[13]),"+f"(d[14]),"+f"(d[15]),"+f"(d[16]),"+f"(d[17]),"+f"(d[18]),"+f"(d[19]),"+f"(d[20]),"+f"(d[21]),"+f"(d[22]),"+f"(d[23]) : "l"(da), "l"(db), "r"(sd));
}
template<> __device__ __forceinline__ void wgmma_rs<80,1>(float* d, uint32_t a0, uint32_t a1, uint32_t a2, uint32_t a3, uint64_t db, int sd) {
  asm volatile("{\n.reg .pred p;\nsetp.ne.b32 p, %45, 0;\n"
  "wgmma.mma_async.sync.aligned.m64n80k16.f32.bf16.bf16 {%0,%1,%2,%3,%4,%5,%6,%7,%8,%9,%10,%11,%12,%13,%14,%15,%16,%17,%18,%19,%20,%21,%22,%23,%24,%25,%26,%27,%28,%29,%30,%31,%32,%33,%34,%35,%36,%37,%38,%39}, {%40,%41,%42,%43}, %44, p, 1, 1, 1;\n}\n"
  : "+f"(d[0]),"+f"(d[1]),"+f"(d[2]),"+f"(d[3]),"+f"(d[4]),"+f"(d[5]),"+f"(d[6]),"+f"(d[7]),"+f"(d[8]),"+f"(d[9]),"+f"(d[10]),"+f"(d[11]),"+f"(d[12]),"+f"(d[13]),"+f"(d[14]),"+f"(d[15]),"+f"(d[16]),"+f"(d[17]),"+f"(d[18]),"+f"(d[19]),"+f"(d[20]),"+f"(d[21]),"+f"(d[22]),"+f"(d[23]),"+f"(d[24]),"+f"(d[25]),"+f"(d[26]),"+f"(d[27]),"+f"(d[28]),"+f"(d[29]),"+f"(d[30]),"+f"(d[31]),"+f"(d[32]),"+f"(d[33]),"+f"(d[34]),"+f"(d[35]),"+f"(d[36]),"+f"(d[37]),"+f"(d[38]),"+f"(d[39]) : "r"(a0), "r"(a1), "r"(a2), "r"(a3), "l"(db), "r"(sd));
}
template<> __device__ __forceinline__ void wgmma_ss<32,1,1>(float* d, uint64_t da, uint64_t db, int sd) {
  asm volatile("{\n.reg .pred p;\nsetp.ne.b32 p, %18, 0;\n"
  "wgmma.mma_async.sync.aligned.m64n32k16.f32.bf16.bf16 {%0,%1,%2,%3,%4,%5,%6,%7,%8,%9,%10,%11,%12,%13,%14,%15}, %16, %17, p, 1, 1, 1, 1;\n}\n"
  : "+f"(d[0]),"+f"(d[1]),"+f"(d[2]),"+f"(d[3]),"+f"(d[4]),"+f"(d[5]),"+f"(d[6]),"+f"(d[7]),"+f"(d[8]),"+f"(d[9]),"+f"(d[10]),"+f"(d[11]),"+f"(d[12]),"+f"(d[13]),"+f"(d[14]),"+f"(d[15]) : "l"(da), "l"(db), "r"(sd));
}
template<> __device__ __forceinline__ void wgmma_rs<88,1>(float* d, uint32_t a0, uint32_t a1, uint32_t a2, uint32_t a3, uint64_t db, int sd) {
  asm volatile("{\n.reg .pred p;\nsetp.ne.b32 p, %49, 0;\n"
  "wgmma.mma_async.sync.aligned.m64n88k16.f32.bf16.bf16 {%0,%1,%2,%3,%4,%5,%6,%7,%8,%9,%10,%11,%12,%13,%14,%15,%16,%17,%18,%19,%20,%21,%22,%23,%24,%25,%26,%27,%28,%29,%30,%31,%32,%33,%34,%35,%36,%37,%38,%39,%40,%41,%42,%43}, {%44,%45,%46,%47}, %48, p, 1, 1, 1;\n}\n"
  : "+f"(d[0]),"+f"(d[1]),"+f"(d[2]),"+f"(d[3]),"+f"(d[4]),"+f"(d[5]),"+f"(d[6]),"+f"(d[7]),"+f"(d[8]),"+f"(d[9]),"+f"(d[10]),"+f"(d[11]),"+f"(d[12]),"+f"(d[13]),"+f"(d[14]),"+f"(d[15]),"+f"(d[16]),"+f"(d[17]),"+f"(d[18]),"+f"(d[19]),"+f"(d[20]),"+f"(d[21]),"+f"(d[22]),"+f"(d[23]),"+f"(d[24]),"+f"(d[25]),"+f"(d[26]),"+f"(d[27]),"+f"(d[28]),"+f"(d[29]),"+f"(d[30]),"+f"(d[31]),"+f"(d[32]),"+f"(d[33]),"+f"(d[34]),"+f"(d[35]),"+f"(d[36]),"+f"(d[37]),"+f"(d[38]),"+f"(d[39]),"+f"(d[40]),"+f"(d[41]),"+f"(d[42]),"+f"(d[43]) : "r"(a0), "r"(a1), "r"(a2), "r"(a3), "l"(db), "r"(sd));
}
template<> __device__ __forceinline__ void wgmma_ss<80,0,1>(float* d, uint64_t da, uint64_t db, int sd) {
  asm volatile("{\n.reg .pred p;\nsetp.ne.b32 p, %42, 0;\n"
  "wgmma.mma_async.sync.aligned.m64n80k16.f32.bf16.bf16 {%0,%1,%2,%3,%4,%5,%6,%7,%8,%9,%10,%11,%12,%13,%14,%15,%16,%17,%18,%19,%20,%21,%22,%23,%24,%25,%26,%27,%28,%29,%30,%31,%32,%33,%34,%35,%36,%37,%38,%39}, %40, %41, p, 1, 1, 0, 1;\n}\n"
  : "+f"(d[0]),"+f"(d[1]),"+f"(d[2]),"+f"(d[3]),"+f"(d[4]),"+f"(d[5]),"+f"(d[6]),"+f"(d[7]),"+f"(d[8]),"+f"(d[9]),"+f"(d[10]),"+f"(d[11]),"+f"(d[12]),"+f"(d[13]),"+f"(d[14]),"+f"(d[15]),"+f"(d[16]),"+f"(d[17]),"+f"(d[18]),"+f"(d[19]),"+f"(d[20]),"+f"(d[21]),"+f"(d[22]),"+f"(d[23]),"+f"(d[24]),"+f"(d[25]),"+f"(d[26]),"+f"(d[27]),"+f"(d[28]),"+f"(d[29]),"+f"(d[30]),"+f"(d[31]),"+f"(d[32]),"+f"(d[33]),"+f"(d[34]),"+f"(d[35]),"+f"(d[36]),"+f"(d[37]),"+f"(d[38]),"+f"(d[39]) : "l"(da), "l"(db), "r"(sd));
}
template<> __device__ __forceinline__ void wgmma_rs<16,0>(float* d, uint32_t a0, uint32_t a1, uint32_t a2, uint32_t a3, uint64_t db, int sd) {
  asm volatile("{\n.reg .pred p;\nsetp.ne.b32 p, %13, 0;\n"
  "wgmma.mma_async.sync.aligned.m64n16k16.f32.bf16.bf16 {%0,%1,%2,%3,%4,%5,%6,%7}, {%8,%9,%10,%11}, %12, p, 1, 1, 0;\n}\n"
  : "+f"(d[0]),"+f"(d[1]),"+f"(d[2]),"+f"(d[3]),"+f"(d[4]),"+f"(d[5]),"+f"(d[6]),"+f"(d[7]) : "r"(a0), "r"(a1), "r"(a2), "r"(a3), "l"(db), "r"(sd));
}
template<> __device__ __forceinline__ void wgmma_rs<32,0>(float* d, uint32_t a0, uint32_t a1, uint32_t a2, uint32_t a3, uint64_t db, int sd) {
  asm volatile("{\n.reg .pred p;\nsetp.ne.b32 p, %21, 0;\n"
  "wgmma.mma_async.sync.aligned.m64n32k16.f32.bf16.bf16 {%0,%1,%2,%3,%4,%5,%6,%7,%8,%9,%10,%11,%12,%13,%14,%15}, {%16,%17,%18,%19}, %20, p, 1, 1, 0;\n}\n"
  : "+f"(d[0]),"+f"(d[1]),"+f"(d[2]),"+f"(d[3]),"+f"(d[4]),"+f"(d[5]),"+f"(d[6]),"+f"(d[7]),"+f"(d[8]),"+f"(d[9]),"+f"(d[10]),"+f"(d[11]),"+f"(d[12]),"+f"(d[13]),"+f"(d[14]),"+f"(d[15]) : "r"(a0), "r"(a1), "r"(a2), "r"(a3), "l"(db), "r"(sd));
}
template<> __device__ __forceinline__ void wgmma_rs<48,0>(float* d, uint32_t a0, uint32_t a1, uint32_t a2, uint32_t a3, uint64_t db, int sd) {
  asm volatile("{\n.reg .pred p;\nsetp.ne.b32 p, %29, 0;\n"
  "wgmma.mma_async.sync.aligned.m64n48k16.f32.bf16.bf16 {%0,%1,%2,%3,%4,%5,%6,%7,%8,%9,%10,%11,%12,%13,%14,%15,%16,%17,%18,%19,%20,%21,%22,%23}, {%24,%25,%26,%27}, %28, p, 1, 1, 0;\n}\n"
  : "+f"(d[0]),"+f"(d[1]),"+f"(d[2]),"+f"(d[3]),"+f"(d[4]),"+f"(d[5]),"+f"(d[6]),"+f"(d[7]),"+f"(d[8]),"+f"(d[9]),"+f"(d[10]),"+f"(d[11]),"+f"(d[12]),"+f"(d[13]),"+f"(d[14]),"+f"(d[15]),"+f"(d[16]),"+f"(d[17]),"+f"(d[18]),"+f"(d[19]),"+f"(d[20]),"+f"(d[21]),"+f"(d[22]),"+f"(d[23]) : "r"(a0), "r"(a1), "r"(a2), "r"(a3), "l"(db), "r"(sd));
}
template<> __device__ __forceinline__ void wgmma_rs<64,0>(float* d, uint32_t a0, uint32_t a1, uint32_t a2, uint32_t a3, uint64_t db, int sd) {
  asm volatile("{\n.reg .pred p;\nsetp.ne.b32 p, %37, 0;\n"
  "wgmma.mma_async.sync.aligned.m64n64k16.f32.bf16.bf16 {%0,%1,%2,%3,%4,%5,%6,%7,%8,%9,%10,%11,%12,%13,%14,%15,%16,%17,%18,%19,%20,%21,%22,%23,%24,%25,%26,%27,%28,%29,%30,%31}, {%32,%33,%34,%35}, %36, p, 1, 1, 0;\n}\n"
  : "+f"(d[0]),"+f"(d[1]),"+f"(d[2]),"+f"(d[3]),"+f"(d[4]),"+f"(d[5]),"+f"(d[6]),"+f"(d[7]),"+f"(d[8]),"+f"(d[9]),"+f"(d[10]),"+f"(d[11]),"+f"(d[12]),"+f"(d[13]),"+f"(d[14]),"+f"(d[15]),"+f"(d[16]),"+f"(d[17]),"+f"(d[18]),"+f"(d[19]),"+f"(d[20]),"+f"(d[21]),"+f"(d[22]),"+f"(d[23]),"+f"(d[24]),"+f"(d[25]),"+f"(d[26]),"+f"(d[27]),"+f"(d[28]),"+f"(d[29]),"+f"(d[30]),"+f"(d[31]) : "r"(a0), "r"(a1), "r"(a2), "r"(a3), "l"(db), "r"(sd));
}
template<> __device__ __forceinline__ void wgmma_rs<80,0>(float* d, uint32_t a0, uint32_t a1, uint32_t a2, uint32_t a3, uint64_t db, int sd) {
  asm volatile("{\n.reg .pred p;\nsetp.ne.b32 p, %45, 0;\n"
  "wgmma.mma_async.sync.aligned.m64n80k16.f32.bf16.bf16 {%0,%1,%2,%3,%4,%5,%6,%7,%8,%9,%10,%11,%12,%13,%14,%15,%16,%17,%18,%19,%20,%21,%22,%23,%24,%25,%26,%27,%28,%29,%30,%31,%32,%33,%34,%35,%36,%37,%38,%39}, {%40,%41,%42,%43}, %44, p, 1, 1, 0;\n}\n"
  : "+f"(d[0]),"+f"(d[1]),"+f"(d[2]),"+f"(d[3]),"+f"(d[4]),"+f"(d[5]),"+f"(d[6]),"+f"(d[7]),"+f"(d[8]),"+f"(d[9]),"+f"(d[10]),"+f"(d[11]),"+f"(d[12]),"+f"(d[13]),"+f"(d[14]),"+f"(d[15]),"+f"(d[16]),"+f"(d[17]),"+f"(d[18]),"+f"(d[19]),"+f"(d[20]),"+f"(d[21]),"+f"(d[22]),"+f"(d[23]),"+f"(d[24]),"+f"(d[25]),"+f"(d[26]),"+f"(d[27]),"+f"(d[28]),"+f"(d[29]),"+f"(d[30]),"+f"(d[31]),"+f"(d[32]),"+f"(d[33]),"+f"(d[34]),"+f"(d[35]),"+f"(d[36]),"+f"(d[37]),"+f"(d[38]),"+f"(d[39]) : "r"(a0), "r"(a1), "r"(a2), "r"(a3), "l"(db), "r"(sd));
}
template<> __device__ __forceinline__ void wgmma_rs<96,0>(float* d, uint32_t a0, uint32_t a1, uint32_t a2, uint32_t a3, uint64_t db, int sd) {
  asm volatile("{\n.reg .pred p;\nsetp.ne.b32 p, %53, 0;\n"
  "wgmma.mma_async.sync.aligned.m64n96k16.f32.bf16.bf16 {%0,%1,%2,%3,%4,%5,%6,%7,%8,%9,%10,%11,%12,%13,%14,%15,%16,%17,%18,%19,%20,%21,%22,%23,%24,%25,%26,%27,%28,%29,%30,%31,%32,%33,%34,%35,%36,%37,%38,%39,%40,%41,%42,%43,%44,%45,%46,%47}, {%48,%49,%50,%51}, %52, p, 1, 1, 0;\n}\n"
  : "+f"(d[0]),"+f"(d[1]),"+f"(d[2]),"+f"(d[3]),"+f"(d[4]),"+f"(d[5]),"+f"(d[6]),"+f"(d[7]),"+f"(d[8]),"+f"(d[9]),"+f"(d[10]),"+f"(d[11]),"+f"(d[12]),"+f"(d[13]),"+f"(d[14]),"+f"(d[15]),"+f"(d[16]),"+f"(d[17]),"+f"(d[18]),"+f"(d[19]),"+f"(d[20]),"+f"(d[21]),"+f"(d[22]),"+f"(d[23]),"+f"(d[24]),"+f"(d[25]),"+f"(d[26]),"+f"(d[27]),"+f"(d[28]),"+f"(d[29]),"+f"(d[30]),"+f"(d[31]),"+f"(d[32]),"+f"(d[33]),"+f"(d[34]),"+f"(d[35]),"+f"(d[36]),"+f"(d[37]),"+f"(d[38]),"+f"(d[39]),"+f"(d[40]),"+f"(d[41]),"+f"(d[42]),"+f"(d[43]),"+f"(d[44]),"+f"(d[45]),"+f"(d[46]),"+f"(d[47]) : "r"(a0), "r"(a1), "r"(a2), "r"(a3), "l"(db), "r"(sd));
}
template<> __device__ __forceinline__ void wgmma_rs<112,0>(float* d, uint32_t a0, uint32_t a1, uint32_t a2, uint32_t a3, uint64_t db, int sd) {
  asm volatile("{\n.reg .pred p;\nsetp.ne.b32 p, %61, 0;\n"
  "wgmma.mma_async.sync.aligned.m64n112k16.f32.bf16.bf16 {%0,%1,%2,%3,%4,%5,%6,%7,%8,%9,%10,%11,%12,%13,%14,%15,%16,%17,%18,%19,%20,%21,%22,%23,%24,%25,%26,%27,%28,%29,%30,%31,%32,%33,%34,%35,%36,%37,%38,%39,%40,%41,%42,%43,%44,%45,%46,%47,%48,%49,%50,%51,%52,%53,%54,%55}, {%56,%57,%58,%59}, %60, p, 1, 1, 0;\n}\n"
  : "+f"(d[0]),"+f"(d[1]),"+f"(d[2]),"+f"(d[3]),"+f"(d[4]),"+f"(d[5]),"+f"(d[6]),"+f"(d[7]),"+f"(d[8]),"+f"(d[9]),"+f"(d[10]),"+f"(d[11]),"+f"(d[12]),"+f"(d[13]),"+f"(d[14]),"+f"(d[15]),"+f"(d[16]),"+f"(d[17]),"+f"(d[18]),"+f"(d[19]),"+f"(d[20]),"+f"(d[21]),"+f"(d[22]),"+f"(d[23]),"+f"(d[24]),"+f"(d[25]),"+f"(d[26]),"+f"(d[27]),"+f"(d[28]),"+f"(d[29]),"+f"(d[30]),"+f"(d[31]),"+f"(d[32]),"+f"(d[33]),"+f"(d[34]),"+f"(d[35]),"+f"(d[36]),"+f"(d[37]),"+f"(d[38]),"+f"(d[39]),"+f"(d[40]),"+f"(d[41]),"+f"(d[42]),"+f"(d[43]),"+f"(d[44]),"+f"(d[45]),"+f"(d[46]),"+f"(d[47]),"+f"(d[48]),"+f"(d[49]),"+f"(d[50]),"+f"(d[51]),"+f"(d[52]),"+f"(d[53]),"+f"(d[54]),"+f"(d[55]) : "r"(a0), "r"(a1), "r"(a2), "r"(a3), "l"(db), "r"(sd));
}
template<> __device__ __forceinline__ void wgmma_rs<128,0>(float* d, uint32_t a0, uint32_t a1, uint32_t a2, uint32_t a3, uint64_t db, int sd) {
  asm volatile("{\n.reg .pred p;\nsetp.ne.b32 p, %69, 0;\n"
  "wgmma.mma_async.sync.aligned.m64n128k16.f32.bf16.bf16 {%0,%1,%2,%3,%4,%5,%6,%7,%8,%9,%10,%11,%12,%13,%14,%15,%16,%17,%18,%19,%20,%21,%22,%23,%24,%25,%26,%27,%28,%29,%30,%31,%32,%33,%34,%35,%36,%37,%38,%39,%40,%41,%42,%43,%44,%45,%46,%47,%48,%49,%50,%51,%52,%53,%54,%55,%56,%57,%58,%59,%60,%61,%62,%63}, {%64,%65,%66,%67}, %68, p, 1, 1, 0;\n}\n"
  : "+f"(d[0]),"+f"(d[1]),"+f"(d[2]),"+f"(d[3]),"+f"(d[4]),"+f"(d[5]),"+f"(d[6]),"+f"(d[7]),"+f"(d[8]),"+f"(d[9]),"+f"(d[10]),"+f"(d[11]),"+f"(d[12]),"+f"(d[13]),"+f"(d[14]),"+f"(d[15]),"+f"(d[16]),"+f"(d[17]),"+f"(d[18]),"+f"(d[19]),"+f"(d[20]),"+f"(d[21]),"+f"(d[22]),"+f"(d[23]),"+f"(d[24]),"+f"(d[25]),"+f"(d[26]),"+f"(d[27]),"+f"(d[28]),"+f"(d[29]),"+f"(d[30]),"+f"(d[31]),"+f"(d[32]),"+f"(d[33]),"+f"(d[34]),"+f"(d[35]),"+f"(d[36]),"+f"(d[37]),"+f"(d[38]),"+f"(d[39]),"+f"(d[40]),"+f"(d[41]),"+f"(d[42]),"+f"(d[43]),"+f"(d[44]),"+f"(d[45]),"+f"(d[46]),"+f"(d[47]),"+f"(d[48]),"+f"(d[49]),"+f"(d[50]),"+f"(d[51]),"+f"(d[52]),"+f"(d[53]),"+f"(d[54]),"+f"(d[55]),"+f"(d[56]),"+f"(d[57]),"+f"(d[58]),"+f"(d[59]),"+f"(d[60]),"+f"(d[61]),"+f"(d[62]),"+f"(d[63]) : "r"(a0), "r"(a1), "r"(a2), "r"(a3), "l"(db), "r"(sd));
}

namespace {
typedef __nv_bfloat16 bf16;
constexpr int OFF_S    = 1024;
constexpr int STG      = 49152;
constexpr int STG_TX   = 47104 + 128;
constexpr int OFF_PHIK = OFF_S - 128;
constexpr int PHIK_HS  = 10240 + 32;
constexpr int OFF_VB   = OFF_S + 49152;
constexpr int OFF_WO   = OFF_S + 75776;
constexpr int OFF_WOT  = OFF_S + 126976;
constexpr int OFF_PHI  = OFF_S + 147456;
constexpr int OFF_KVB  = OFF_PHI + 12800;
constexpr int KVB_S    = 2592;
constexpr int OFF_KA   = OFF_KVB;
constexpr int OFF_KB   = OFF_KVB + 16384;
constexpr int OFF_U    = OFF_KVB + 28672;
constexpr int OFF_XS   = OFF_U;
constexpr int OFF_KT   = OFF_U + 8960;
constexpr int OFF_P    = OFF_KT + 16640;
constexpr int OFF_KR   = OFF_P + 4160;
constexpr int OFF_KV16 = OFF_KR + 5184;
constexpr int OFF_G    = 256;
constexpr int OFF_KX   = OFF_S + 40960;
constexpr int SMEM_BYTES = OFF_P + 16384;
static_assert(SMEM_BYTES <= 232448, "smem");
constexpr int B_FULL = 0, B_EMPTY = 24, B_FULLO = 48, B_EMPTYO = 80, B_WO = 112, B_Y = 120, B_FULLU = 128, B_XS = 144, B_Z = 152, B_T = 160, B_KX = 168;
constexpr int C_X = 0, C_Y = 8, C_KV = 16, C_O = 40, C_DONE = 56, C_NUM = 64;

struct Scratch {
  unsigned char xT[640 * 4096];
  unsigned char y[16 * 640 * 256];
  unsigned char o[16 * 8 * 20480];
  float kv[8 * 2 * 2560];
  float gate[16 * 128];
  unsigned cnt[C_NUM * 32];
};
__device__ __align__(1024) Scratch g_s;
#define STAMP(i)
#define STAMPW(i)

constexpr int SPIN_MAX = 1 << 22;
__device__ __forceinline__ uint32_t smem_u32(const void* p) { return (uint32_t)__cvta_generic_to_shared(p); }
__device__ __forceinline__ void mbar_init(uint32_t bar, int cnt) { asm volatile("mbarrier.init.shared::cta.b64 [%0], %1;" ::"r"(bar), "r"(cnt)); }
__device__ __forceinline__ void mbar_expect(uint32_t bar, int bytes) { asm volatile("mbarrier.arrive.expect_tx.shared::cta.b64 _, [%0], %1;" ::"r"(bar), "r"(bytes) : "memory"); }
__device__ __forceinline__ void mbar_arrive(uint32_t bar) { asm volatile("mbarrier.arrive.shared::cta.b64 _, [%0];" ::"r"(bar) : "memory"); }
__device__ __forceinline__ void mbar_arrive_cl(uint32_t bar, uint32_t cta) {
  asm volatile("{\n.reg .b32 ra;\nmapa.shared::cluster.u32 ra, %0, %1;\nmbarrier.arrive.shared::cluster.b64 _, [ra];\n}\n" ::"r"(bar), "r"(cta) : "memory");
}
__device__ __forceinline__ bool mbar_try(uint32_t bar, int parity) {
  uint32_t ok;
  asm volatile("{\n.reg .pred p;\nmbarrier.try_wait.parity.shared::cta.b64 p, [%1], %2;\nselp.u32 %0, 1, 0, p;\n}\n" : "=r"(ok) : "r"(bar), "r"(parity) : "memory");
  return ok;
}
__device__ __forceinline__ void mbar_wait(uint32_t bar, int parity) {
  int n = 0;
  while (!mbar_try(bar, parity)) { if (++n > SPIN_MAX) __trap(); }
}
__device__ __forceinline__ unsigned ld_acq(const unsigned* p) { unsigned v; asm volatile("ld.acquire.gpu.global.u32 %0, [%1];" : "=r"(v) : "l"(p) : "memory"); return v; }
__device__ __forceinline__ void poll(const unsigned* p, unsigned target) {
  int n = 0;
  while ((int)(ld_acq(p) - target) < 0) { if (++n > SPIN_MAX) __trap(); }
}
__device__ __forceinline__ void red_rel(unsigned* p) { asm volatile("red.release.gpu.global.add.u32 [%0], 1;" ::"l"(p) : "memory"); }
__device__ __forceinline__ void red_rlx(unsigned* p) { asm volatile("red.relaxed.gpu.global.add.u32 [%0], 1;" ::"l"(p) : "memory"); }
__device__ __forceinline__ void fence_async() { asm volatile("fence.proxy.async.shared::cta;" ::: "memory"); }
__device__ __forceinline__ void fence_async_g() { asm volatile("fence.proxy.async.global;" ::: "memory"); }
__device__ __forceinline__ void bar_sync(int id, int n) { asm volatile("bar.sync %0, %1;" ::"r"(id), "r"(n) : "memory"); }
__device__ __forceinline__ void bar_arrive(int id, int n) { asm volatile("bar.arrive %0, %1;" ::"r"(id), "r"(n) : "memory"); }
__device__ __forceinline__ void wg_fence() { asm volatile("wgmma.fence.sync.aligned;" ::: "memory"); }
__device__ __forceinline__ void wg_commit() { asm volatile("wgmma.commit_group.sync.aligned;" ::: "memory"); }
template <int N> __device__ __forceinline__ void wg_wait() { asm volatile("wgmma.wait_group.sync.aligned %0;" ::"n"(N) : "memory"); }
template <int N> __device__ __forceinline__ void reg_fence(float* d) {
#pragma unroll
  for (int i = 0; i < N; i++) asm volatile("" : "+f"(d[i])::"memory");
}
template <int N> __device__ __forceinline__ void reg_fence(uint32_t* d) {
#pragma unroll
  for (int i = 0; i < N; i++) asm volatile("" : "+r"(d[i])::"memory");
}
__device__ __forceinline__ uint64_t mkdesc(uint32_t addr, uint32_t lbo, uint32_t sbo, uint32_t swz) {
  return (uint64_t)((addr >> 4) & 0x3FFF) | ((uint64_t)(lbo >> 4) << 16) | ((uint64_t)(sbo >> 4) << 32) | ((uint64_t)swz << 62);
}
__device__ __forceinline__ uint32_t pack(float lo, float hi) { uint32_t r; asm("cvt.rn.bf16x2.f32 %0, %1, %2;" : "=r"(r) : "f"(hi), "f"(lo)); return r; }
__device__ __forceinline__ float blo(uint32_t v) { return __uint_as_float(v << 16); }
__device__ __forceinline__ float bhi(uint32_t v) { return __uint_as_float(v & 0xFFFF0000u); }
__device__ __forceinline__ float ex2(float x) { float r; asm("ex2.approx.ftz.f32 %0, %1;" : "=f"(r) : "f"(x)); return r; }
__device__ __forceinline__ float rcp(float x) { float r; asm("rcp.approx.ftz.f32 %0, %1;" : "=f"(r) : "f"(x)); return r; }
__device__ __forceinline__ void sts32(uint32_t a, uint32_t v) { asm volatile("st.shared.u32 [%0], %1;" ::"r"(a), "r"(v) : "memory"); }
__device__ __forceinline__ void sts64f(uint32_t a, float x, float y) { asm volatile("st.shared.v2.f32 [%0], {%1,%2};" ::"r"(a), "f"(x), "f"(y) : "memory"); }
__device__ __forceinline__ void sts128(uint32_t a, uint32_t x, uint32_t y, uint32_t z, uint32_t w) { asm volatile("st.shared.v4.u32 [%0], {%1,%2,%3,%4};" ::"r"(a), "r"(x), "r"(y), "r"(z), "r"(w) : "memory"); }
__device__ __forceinline__ uint32_t lds32(uint32_t a) { uint32_t v; asm volatile("ld.shared.u32 %0, [%1];" : "=r"(v) : "r"(a) : "memory"); return v; }
__device__ __forceinline__ uint32_t lds16(uint32_t a) { uint16_t v; asm volatile("ld.shared.u16 %0, [%1];" : "=h"(v) : "r"(a) : "memory"); return v; }
__device__ __forceinline__ uint4 lds128(uint32_t a) { uint4 v; asm volatile("ld.shared.v4.u32 {%0,%1,%2,%3}, [%4];" : "=r"(v.x), "=r"(v.y), "=r"(v.z), "=r"(v.w) : "r"(a) : "memory"); return v; }
__device__ __forceinline__ float4 lds128f(uint32_t a) { float4 v; asm volatile("ld.shared.v4.f32 {%0,%1,%2,%3}, [%4];" : "=f"(v.x), "=f"(v.y), "=f"(v.z), "=f"(v.w) : "r"(a) : "memory"); return v; }
__device__ __forceinline__ void stsm4(uint32_t a, uint32_t r0, uint32_t r1, uint32_t r2, uint32_t r3) { asm volatile("stmatrix.sync.aligned.m8n8.x4.shared.b16 [%0], {%1,%2,%3,%4};" ::"r"(a), "r"(r0), "r"(r1), "r"(r2), "r"(r3) : "memory"); }
__device__ __forceinline__ void stsm4t(uint32_t a, uint32_t r0, uint32_t r1, uint32_t r2, uint32_t r3) { asm volatile("stmatrix.sync.aligned.m8n8.x4.trans.shared.b16 [%0], {%1,%2,%3,%4};" ::"r"(a), "r"(r0), "r"(r1), "r"(r2), "r"(r3) : "memory"); }
__device__ __forceinline__ uint4 ldsm4t(uint32_t a) { uint4 v; asm volatile("ldmatrix.sync.aligned.m8n8.x4.trans.shared.b16 {%0,%1,%2,%3}, [%4];" : "=r"(v.x), "=r"(v.y), "=r"(v.z), "=r"(v.w) : "r"(a) : "memory"); return v; }
__device__ __forceinline__ void tma2d(uint32_t dst, const CUtensorMap* m, int c0, int c1, uint32_t bar) {
  asm volatile("cp.async.bulk.tensor.2d.shared::cluster.global.mbarrier::complete_tx::bytes [%0], [%1, {%3,%4}], [%2];" ::"r"(dst), "l"(m), "r"(bar), "r"(c0), "r"(c1) : "memory");
}
__device__ __forceinline__ void tma3d_mc(uint32_t dst, const CUtensorMap* m, int c0, int c1, int c2, uint32_t bar) {
  asm volatile("cp.async.bulk.tensor.3d.shared::cluster.global.mbarrier::complete_tx::bytes.multicast::cluster [%0], [%1, {%3,%4,%5}], [%2], %6;" ::"r"(dst), "l"(m), "r"(bar), "r"(c0), "r"(c1), "r"(c2), "h"((uint16_t)3) : "memory");
}
__device__ __forceinline__ void tma5d(uint32_t dst, const CUtensorMap* m, int c0, int c1, int c2, int c3, int c4, uint32_t bar) {
  asm volatile("cp.async.bulk.tensor.5d.shared::cluster.global.mbarrier::complete_tx::bytes [%0], [%1, {%3,%4,%5,%6,%7}], [%2];" ::"r"(dst), "l"(m), "r"(bar), "r"(c0), "r"(c1), "r"(c2), "r"(c3), "r"(c4) : "memory");
}
__device__ __forceinline__ void bulk_ld(uint32_t dst, const void* src, int bytes, uint32_t bar) {
  asm volatile("cp.async.bulk.shared::cluster.global.mbarrier::complete_tx::bytes [%0], [%1], %2, [%3];" ::"r"(dst), "l"(src), "r"(bytes), "r"(bar) : "memory");
}
__device__ __forceinline__ void bulk_ld_mc(uint32_t dst, const void* src, int bytes, uint32_t bar) {
  asm volatile("cp.async.bulk.shared::cluster.global.mbarrier::complete_tx::bytes.multicast::cluster [%0], [%1], %2, [%3], %4;" ::"r"(dst), "l"(src), "r"(bytes), "r"(bar), "h"((uint16_t)3) : "memory");
}
__device__ __forceinline__ void tma_st2d(const CUtensorMap* m, uint32_t src, int c0, int c1) {
  asm volatile("cp.async.bulk.tensor.2d.global.shared::cta.bulk_group [%0, {%2,%3}], [%1];" ::"l"(m), "r"(src), "r"(c0), "r"(c1) : "memory");
}
__device__ __forceinline__ void red4(float* p, float a, float b, float c) { asm volatile("red.relaxed.gpu.global.add.v4.f32 [%0], {%1,%2,%3,%4};" ::"l"(p), "f"(a), "f"(b), "f"(c), "f"(1.f) : "memory"); }
__device__ __forceinline__ float4 ld_rlx4(const float* p) { float4 v; asm volatile("ld.relaxed.gpu.global.v4.f32 {%0,%1,%2,%3}, [%4];" : "=f"(v.x), "=f"(v.y), "=f"(v.z), "=f"(v.w) : "l"(p) : "memory"); return v; }
__device__ __forceinline__ unsigned ld_rlx(const unsigned* p) { unsigned v; asm volatile("ld.relaxed.gpu.global.u32 %0, [%1];" : "=r"(v) : "l"(p) : "memory"); return v; }
__device__ __forceinline__ void sts64(uint32_t a, uint32_t x, uint32_t y) { asm volatile("st.shared.v2.u32 [%0], {%1,%2};" ::"r"(a), "r"(x), "r"(y) : "memory"); }
__device__ __forceinline__ uint2 lds64(uint32_t a) { uint2 v; asm volatile("ld.shared.v2.u32 {%0,%1}, [%2];" : "=r"(v.x), "=r"(v.y) : "r"(a) : "memory"); return v; }
__device__ __forceinline__ uint32_t mapa(uint32_t a, uint32_t cta) { uint32_t r; asm("mapa.shared::cluster.u32 %0, %1, %2;" : "=r"(r) : "r"(a), "r"(cta)); return r; }
__device__ __forceinline__ void st_async4(uint32_t a, float x, float y, float z, float w, uint32_t bar) {
  asm volatile("st.async.weak.shared::cluster.mbarrier::complete_tx::bytes.v4.f32 [%0], {%1,%2,%3,%4}, [%5];" ::"r"(a), "f"(x), "f"(y), "f"(z), "f"(w), "r"(bar) : "memory");
}
__device__ __forceinline__ void cl_arrive() { asm volatile("barrier.cluster.arrive.relaxed.aligned;" ::: "memory"); }
__device__ __forceinline__ void cl_wait() { asm volatile("barrier.cluster.wait.acquire.aligned;" ::: "memory"); }
__device__ __forceinline__ float bf2f(uint16_t v) { return __uint_as_float((uint32_t)v << 16); }
__device__ __forceinline__ float rbf(float x) { return __bfloat162float(__float2bfloat16_rn(x)); }

__device__ __forceinline__ void softmax2(const float* p, uint32_t* ph0, uint32_t* ph1) {
  constexpr float L = 1.4426950408889634f;
#pragma unroll
  for (int r = 0; r < 2; r++) {
    uint32_t* ph = r ? ph1 : ph0;
    float mx = fmaxf(p[2 * r], p[2 * r + 1]), mn = fminf(p[2 * r], p[2 * r + 1]);
#pragma unroll
    for (int j = 1; j < 10; j++) {
      mx = fmaxf(mx, fmaxf(p[4 * j + 2 * r], p[4 * j + 2 * r + 1]));
      mn = fminf(mn, fminf(p[4 * j + 2 * r], p[4 * j + 2 * r + 1]));
    }
    const float mxl = -mx * L, mnl = mn * L;
    float e[20], s0 = 0.f, s1 = 0.f;
#pragma unroll
    for (int j = 0; j < 10; j++) {
      e[2 * j] = ex2(fmaf(p[4 * j + 2 * r], L, mxl));
      e[2 * j + 1] = ex2(fmaf(p[4 * j + 2 * r + 1], L, mxl));
      s0 += e[2 * j]; s1 += e[2 * j + 1];
    }
    float rs = rcp(s0 + s1);
#pragma unroll
    for (int j = 0; j < 10; j++) ph[j] = pack(e[2 * j] * rs, e[2 * j + 1] * rs);
    s0 = 0.f; s1 = 0.f;
#pragma unroll
    for (int j = 0; j < 10; j++) {
      e[2 * j] = ex2(fmaf(p[4 * j + 2 * r], -L, mnl));
      e[2 * j + 1] = ex2(fmaf(p[4 * j + 2 * r + 1], -L, mnl));
      s0 += e[2 * j]; s1 += e[2 * j + 1];
    }
    rs = rcp(s0 + s1);
#pragma unroll
    for (int j = 0; j < 10; j++) ph[10 + j] = pack(e[2 * j] * rs, e[2 * j + 1] * rs);
  }
}

struct cf { float x, y; };
__device__ __forceinline__ cf cexpp(float a2, float be, float p) {
  float m = ex2(a2 * p), th = be * p;
  return cf{m * __cosf(th), m * __sinf(th)};
}
__device__ __forceinline__ cf cmul(cf a, cf b) { return cf{fmaf(a.x, b.x, -a.y * b.y), fmaf(a.x, b.y, a.y * b.x)}; }

template <int SH> __device__ __forceinline__ void expand16(uint32_t kv, int base, uint32_t dst) {
  constexpr int NV = (16 >> SH) + 1;
  uint32_t v[NV];
#pragma unroll
  for (int i = 0; i < NV; i++) v[i] = (SH == 0 && i == 0) ? 0u : lds16(kv + 2 * (base + i));
  uint32_t w[8];
#pragma unroll
  for (int i = 0; i < 8; i++) {
    int q[2];
#pragma unroll
    for (int h = 0; h < 2; h++) {
      int e = 16 - (2 * i + h);
      int qq = e >> SH, rem = e & ((1 << SH) - 1), half = (1 << SH) >> 1;
      if (SH > 0 && (rem > half || (rem == half && (qq & 1)))) qq++;
      q[h] = qq;
    }
    w[i] = v[q[0]] | (v[q[1]] << 16);
  }
  sts128(dst, w[0], w[1], w[2], w[3]);
  sts128(dst + 16, w[4], w[5], w[6], w[7]);
}

template <int G> __device__ __forceinline__ void conv_load(uint32_t ka, uint32_t* a) {
#pragma unroll
  for (int h = 0; h < 2; h++) {
    const uint32_t ad = ka - 128 * (2 * G + h);
    uint32_t wm = lds32(ad - 4), w0 = lds32(ad), w1 = lds32(ad + 4);
    a[4 * h + 0] = w0; a[4 * h + 1] = __byte_perm(wm, w0, 0x5432);
    a[4 * h + 2] = w1; a[4 * h + 3] = __byte_perm(w0, w1, 0x5432);
  }
  reg_fence<8>(a);
}
template <int G> struct ConvLoop {
  static __device__ __forceinline__ void run(float* acc, uint32_t ka, uint64_t db, uint32_t* cur, uint32_t* nxt) {
    wg_fence();
    wgmma_rs<128 - 16 * (G / 2), 0>(acc, cur[0], cur[1], cur[2], cur[3], db + 8 * G, 1);
    wgmma_rs<128 - 16 * (G / 2), 0>(acc, cur[4], cur[5], cur[6], cur[7], db + 8 * G + 4, 1);
    wg_commit();
    if (G < 15) {
      wg_wait<1>();
      conv_load<G + 1>(ka, nxt);
      ConvLoop<G + 1>::run(acc, ka, db, nxt, cur);
    }
  }
};
template <> struct ConvLoop<16> { static __device__ __forceinline__ void run(float*, uint32_t, uint64_t, uint32_t*, uint32_t*) {} };

struct KPrep { cf T[8], S[4]; uint32_t B[22]; };
__device__ __forceinline__ void kprep(KPrep& k, uint16_t n_lar, uint16_t n_aim, uint16_t n_cre, uint16_t n_cim, uint16_t n_ldt) {
  const float dt = rbf(expf(bf2f(n_ldt)));
  const float a2 = -rbf(expf(bf2f(n_lar))) * dt * 1.4426950408889634f, be = bf2f(n_aim) * dt;
  cf z[8];
  z[1] = cexpp(a2, be, 1.f);
  k.T[1] = cexpp(a2, -be, 8.f);
  const cf z64 = cexpp(a2, -be, 64.f), z256 = cexpp(a2, be, 256.f), z1024 = cexpp(a2, be, 1024.f);
  z[2] = cmul(z[1], z[1]); z[3] = cmul(z[2], z[1]); z[4] = cmul(z[2], z[2]);
  z[5] = cmul(z[4], z[1]); z[6] = cmul(z[4], z[2]); z[7] = cmul(z[4], z[3]);
  k.T[2] = cmul(k.T[1], k.T[1]); k.T[3] = cmul(k.T[2], k.T[1]); k.T[4] = cmul(k.T[2], k.T[2]);
  k.T[5] = cmul(k.T[4], k.T[1]); k.T[6] = cmul(k.T[4], k.T[2]); k.T[7] = cmul(k.T[4], k.T[3]);
  k.S[0] = cf{2.f * (bf2f(n_cre) * dt), -2.f * (bf2f(n_cim) * dt)};
  k.S[1] = cmul(k.S[0], z64); k.S[2] = cmul(k.S[1], z64); k.S[3] = cmul(k.S[2], z64);
  k.B[0] = pack(1.f, z[1].x); k.B[4] = pack(0.f, z[1].y);
#pragma unroll
  for (int i = 1; i < 4; i++) { k.B[i] = pack(z[2 * i].x, z[2 * i + 1].x); k.B[4 + i] = pack(z[2 * i].y, z[2 * i + 1].y); }
  const cf z512 = cmul(z256, z256), z768 = cmul(z512, z256);
  cf a = cmul(z256, z[2]);
  k.B[8] = pack(z256.x, a.x); k.B[12] = pack(z256.y, a.y);
  a = cmul(z256, z[4]);
  cf b = cmul(z256, z[6]);
  k.B[9] = pack(a.x, b.x); k.B[13] = pack(a.y, b.y);
  a = cmul(z512, z[4]);
  k.B[10] = pack(z512.x, a.x); k.B[14] = pack(z512.y, a.y);
  a = cmul(z768, z[4]);
  k.B[11] = pack(z768.x, a.x); k.B[15] = pack(z768.y, a.y);
  a = cmul(z1024, z256);
  k.B[16] = pack(z1024.x, a.x); k.B[19] = pack(z1024.y, a.y);
  a = cmul(z1024, z512); b = cmul(z1024, z768);
  k.B[17] = pack(a.x, b.x); k.B[20] = pack(a.y, b.y);
  a = cmul(z1024, z1024);
  k.B[18] = pack(a.x, 0.f); k.B[21] = pack(a.y, 0.f);
}

struct Params {
  Scratch* s;
  const uint16_t *wo, *lar, *aim, *cre, *cim, *ldt, *dsk;
  const uint32_t* wphi;
  const uint2* gw;
  const unsigned char *x, *w;
};

__global__ void __cluster_dims__(2, 1, 1) __launch_bounds__(512, 1)
fused_kernel(const __grid_constant__ Params prm, const __grid_constant__ CUtensorMap tmX, const __grid_constant__ CUtensorMap tmW,
             const __grid_constant__ CUtensorMap tmWt, const __grid_constant__ CUtensorMap tmXs, const __grid_constant__ CUtensorMap tmWo,
             const __grid_constant__ CUtensorMap tmOut) {
  extern __shared__ __align__(1024) unsigned char smem_raw[];
  const uint32_t sb = smem_u32(smem_raw);
  const int tid = threadIdx.x, lane = tid & 31;
  const int warp = __shfl_sync(0xffffffffu, tid >> 5, 0);
  const int g = lane >> 2, t = lane & 3;
  const int cta = blockIdx.x, rank = cta & 1, cl = cta >> 1;
  const int cg = cl & 7, rt = 2 * (cl >> 3) + rank;
  const int rt3 = 2 * (cl >> 3) + (cg & 1), ct3 = (cg & 6) + rank;
  unsigned* const cnt = prm.s->cnt;

  if (warp == 12) {
    if (lane == 0) {
      for (int i = 0; i < 3; i++) { mbar_init(sb + B_FULL + 8 * i, 1); mbar_init(sb + B_EMPTY + 8 * i, 16); }
      for (int i = 0; i < 4; i++) { mbar_init(sb + B_FULLO + 8 * i, 1); mbar_init(sb + B_EMPTYO + 8 * i, 16); }
      mbar_init(sb + B_WO, 4); mbar_init(sb + B_Y, 1); mbar_init(sb + B_FULLU, 1); mbar_init(sb + B_FULLU + 8, 1);
      mbar_init(sb + B_XS, 1); mbar_init(sb + B_Z, 1); mbar_init(sb + B_T, 1); mbar_init(sb + B_KX, 1);
      asm volatile("fence.mbarrier_init.release.cluster;" ::: "memory");
    }
    __syncwarp();
    cl_arrive();
    if (lane == 0) {
      for (int kb = 0; kb < 3; kb++) {
        mbar_expect(sb + B_FULL + 8 * kb, STG_TX);
        tma2d(sb + OFF_S + ((3 - kb) % 3) * STG, &tmX, 64 * kb, 128 * rt, sb + B_FULL + 8 * kb);
        bulk_ld(sb + OFF_S + ((3 - kb) % 3) * STG + 31744, prm.gw + 16 * kb, 128, sb + B_FULL + 8 * kb);
      }
    }
    __syncwarp();
    cl_wait();
    if (lane == 0) {
      for (int kb = 0; kb < 3; kb++) {
        const uint32_t st = sb + OFF_S + ((3 - kb) % 3) * STG + 16384 + rank * 16384;
        tma3d_mc(st, &tmW, 80 * cg, 64 * kb + 32 * rank, 0, sb + B_FULL + 8 * kb);
        tma3d_mc(st + 12288, &tmWt, 80 * cg + 64, 64 * kb + 32 * rank, 0, sb + B_FULL + 8 * kb);
      }
      mbar_expect(sb + B_XS, 20480);
      tma2d(sb + OFF_XS, &tmXs, 80 * cg, 128 * rt, sb + B_XS);
      mbar_expect(sb + B_KX, 7680);
    }
    __syncwarp();
    STAMPW(64);
  } else {
    if (tid == 416) {
      asm volatile("prefetch.tensormap [%0];" ::"l"(&tmX) : "memory");
      asm volatile("prefetch.tensormap [%0];" ::"l"(&tmW) : "memory");
      asm volatile("prefetch.tensormap [%0];" ::"l"(&tmWt) : "memory");
      asm volatile("prefetch.tensormap [%0];" ::"l"(&tmXs) : "memory");
    }
    if (tid < 128) asm volatile("prefetch.global.L2 [%0];" ::"l"(prm.x + (128 * rt + tid) * 1280));
    else if (tid < 320) asm volatile("prefetch.global.L2 [%0];" ::"l"(prm.w + (32 * rank + (tid & 31)) * 3840 + ((tid >> 6) - 2) * 1280 + 160 * cg + (tid & 32) * 4));
    __syncwarp();
    cl_arrive();
  }

  if (warp < 8) {
    const int wg = warp >> 2, w = warp & 3;
    {
      uint32_t wv[4];
#pragma unroll
      for (int i = 0; i < 4; i++) { int idx = tid + 256 * i; wv[i] = idx < 800 ? __ldg(prm.wphi + cg * 800 + idx) : 0u; }
#pragma unroll
      for (int i = 0; i < 4; i++) { int idx = tid + 256 * i; if (idx < 800) sts128(sb + OFF_PHI + idx * 16, 0, 0, 0, 0); }
      bar_sync(1, 256);
      if (tid == 0) STAMP(65);
#pragma unroll
      for (int i = 0; i < 4; i++) {
        int idx = tid + 256 * i;
        if (idx < 800) {
          int kk = idx / 10, j = idx - kk * 10, h = kk / 20;
          sts32(sb + OFF_PHI + j * 1280 + kk * 16 + h * 4, wv[i]);
        }
      }
      fence_async();
    }
    asm volatile("setmaxnreg.inc.sync.aligned.u32 176;");
    float acc[120];
#pragma unroll
    for (int i = 0; i < 120; i++) acc[i] = 0.f;
    reg_fence<120>(acc);
    cl_wait();
    STAMPW(0 + warp);
    float gl = 0.f;
    const uint32_t goff = (16 * cg + (tid >> 4)) * 128 + ((((tid >> 1) ^ (tid >> 4)) & 7) * 16) + (tid & 1) * 8;
#pragma unroll 1
    for (int kb = 0; kb < 10; kb++) {
      const int s = kb % 3;
      const uint32_t st = sb + OFF_S + ((3 - s) % 3) * STG;
      mbar_wait(sb + B_FULL + 8 * s, (kb / 3) & 1);
      if (warp == 0) STAMPW(40 + kb);
      const uint64_t da = mkdesc(st + wg * 8192, 16, 1024, 1);
      const uint64_t db = mkdesc(st + 16384, 4096, 1024, 1);
      const uint64_t dt = mkdesc(st + 16384 + 12288, 1024, 256, 3);
      wg_fence();
#pragma unroll
      for (int ks = 0; ks < 4; ks++)
      {
        wgmma_ss<192, 0, 1>(acc, da + 2 * ks, db + (ks >> 1) * 1024 + (ks & 1) * 128, 1);
        wgmma_ss<48, 0, 1>(acc + 96, da + 2 * ks, dt + (ks >> 1) * 1024 + (ks & 1) * 32, 1);
      }
      wg_commit();
      {
        const uint2 xv = lds64(st + goff), gv = lds64(st + 31744 + (tid & 15) * 8);
        gl = fmaf(blo(xv.x), blo(gv.x), gl); gl = fmaf(bhi(xv.x), bhi(gv.x), gl);
        gl = fmaf(blo(xv.y), blo(gv.y), gl); gl = fmaf(bhi(xv.y), bhi(gv.y), gl);
        reg_fence<1>(&gl);
      }
      wg_wait<0>();
      if (lane < 2) mbar_arrive_cl(sb + B_EMPTY + 8 * s, lane);
    }
    reg_fence<120>(acc);
    STAMPW(8 + warp);
    uint32_t ph0[20], ph1[20];
    float pq[40];
    {
      float pk[40];
      const uint64_t dphi = mkdesc(sb + OFF_PHI, 128, 1280, 0);
      const uint32_t rg = (8 * wg + 2 * w) * 128;
      mbar_wait(sb + B_EMPTY + 16, 0);
      {
        uint32_t va[20];
#pragma unroll
        for (int j = 0; j < 10; j++) {
          const int bv = j < 8 ? 16 + j : 20 + j;
          va[2 * j] = pack(acc[4 * bv], acc[4 * bv + 1]); va[2 * j + 1] = pack(acc[4 * bv + 2], acc[4 * bv + 3]);
        }
        const uint32_t v0 = sb + OFF_VB + rg + (lane & 15) * 16;
        const uint32_t hi = lane >> 4;
        stsm4(v0 + (0 + hi) * 2048, va[0], va[1], va[2], va[3]);
        stsm4(v0 + (3 + hi) * 2048, va[4], va[5], va[6], va[7]);
        stsm4(v0 + (5 + hi) * 2048, va[8], va[9], va[10], va[11]);
        stsm4(v0 + (7 + 2 * hi) * 2048, va[12], va[13], va[14], va[15]);
        stsm4(v0 + (10 + hi) * 2048, va[16], va[17], va[18], va[19]);
        sts128(v0 + (2 + 6 * hi) * 2048, 0x3F803F80u, 0x3F803F80u, 0x3F803F80u, 0x3F803F80u);
      }
      uint32_t fq[20];
#pragma unroll
      for (int j = 0; j < 10; j++) {
        const int bq = j < 8 ? j : 16 + j;
        fq[2 * j] = pack(acc[4 * bq], acc[4 * bq + 1]); fq[2 * j + 1] = pack(acc[4 * bq + 2], acc[4 * bq + 3]);
      }
      uint32_t fa[20];
#pragma unroll
      for (int j = 0; j < 10; j++) {
        const int bk = j < 8 ? 8 + j : 18 + j;
        fa[2 * j] = pack(acc[4 * bk], acc[4 * bk + 1]); fa[2 * j + 1] = pack(acc[4 * bk + 2], acc[4 * bk + 3]);
      }
      reg_fence<20>(fa); reg_fence<20>(fq);
      wg_fence();
#pragma unroll
      for (int s = 0; s < 5; s++) wgmma_rs<80, 1>(pk, fa[4 * s], fa[4 * s + 1], fa[4 * s + 2], fa[4 * s + 3], dphi + 16 * s, s > 0);
      wg_commit();
#pragma unroll
      for (int s = 0; s < 5; s++) wgmma_rs<80, 1>(pq, fq[4 * s], fq[4 * s + 1], fq[4 * s + 2], fq[4 * s + 3], dphi + 16 * s, s > 0);
      wg_commit();
      wg_wait<1>();
      reg_fence<40>(pk);
      if (warp == 0) STAMPW(66);
      softmax2(pk, ph0, ph1);
      mbar_wait(sb + B_EMPTY, 1);
      const uint32_t a0 = sb + OFF_PHIK + t * PHIK_HS + rg + g * 16;
#pragma unroll
      for (int c = 0; c < 5; c++) {
        sts128(a0 + c * 2048, ph0[4 * c], ph0[4 * c + 1], ph0[4 * c + 2], ph0[4 * c + 3]);
        sts128(a0 + c * 2048 + 128, ph1[4 * c], ph1[4 * c + 1], ph1[4 * c + 2], ph1[4 * c + 3]);
      }
    }
    fence_async();
    bar_sync(1, 256);
    STAMPW(16 + warp);
    const unsigned ep1 = (ld_rlx(cnt + C_DONE * 32) >> 7) + 1;
    {
      float kv[32];
      wg_fence();
#pragma unroll
      for (int hh = 0; hh < 2; hh++) {
        const uint64_t da = mkdesc(sb + OFF_PHIK + (2 * wg + hh) * PHIK_HS, 128, 2048, 0);
        const uint64_t db = mkdesc(sb + OFF_VB + (6 * wg + 2 * hh) * 2048, 128, 2048, 0);
#pragma unroll
        for (int s = 0; s < 8; s++) wgmma_ss<32, 1, 1>(kv + 16 * hh, da + 16 * s, db + 16 * s, s > 0);
      }
      wg_commit();
      mbar_wait(sb + B_Z, 0);
      wg_wait<0>();
      reg_fence<32>(kv);
      reg_fence<40>(pq);
      if (warp == 0) STAMPW(67);
      if (w < 3) {
        float v[2][12];
#pragma unroll
        for (int r = 0; r < 2; r++) {
          v[r][0] = kv[2 * r]; v[r][1] = kv[2 * r + 1]; v[r][2] = kv[4 + 2 * r]; v[r][3] = kv[5 + 2 * r];
          v[r][4] = t < 2 ? kv[12 + 2 * r] : kv[8 + 2 * r]; v[r][5] = t < 2 ? kv[13 + 2 * r] : 0.f;
          v[r][6] = kv[24 + 2 * r]; v[r][7] = kv[25 + 2 * r]; v[r][8] = kv[28 + 2 * r]; v[r][9] = kv[29 + 2 * r];
          v[r][10] = t < 2 ? kv[16 + 2 * r] : kv[20 + 2 * r]; v[r][11] = t < 2 ? 0.f : kv[21 + 2 * r];
        }
        const uint32_t xa = sb + OFF_KX + w * 3072 + lane * 16;
        if (wg != rank) {
          const uint32_t ra = mapa(xa, wg), rb = mapa(sb + B_KX, wg);
#pragma unroll
          for (int r = 0; r < 2; r++)
            if (r == 0 || w < 2)
#pragma unroll
              for (int i = 0; i < 3; i++) st_async4(ra + r * 1536 + i * 512, v[r][4 * i], v[r][4 * i + 1], v[r][4 * i + 2], v[r][4 * i + 3], rb);
        } else {
          float* b0 = prm.s->kv + (cg * 2 + rank) * 2560 + w * 1024 + lane * 4;
          mbar_wait(sb + B_KX, 0);
          float4 u[2][3];
#pragma unroll
          for (int r = 0; r < 2; r++)
            if (r == 0 || w < 2)
#pragma unroll
              for (int i = 0; i < 3; i++) u[r][i] = lds128f(xa + r * 1536 + i * 512);
#pragma unroll
          for (int r = 0; r < 2; r++)
            if (r == 0 || w < 2) {
              float* b = b0 + r * 512;
              red4(b, v[r][0] + u[r][0].x, v[r][1] + u[r][0].y, v[r][2] + u[r][0].z);
              red4(b + 128, v[r][3] + u[r][0].w, v[r][4] + u[r][1].x, v[r][5] + u[r][1].y);
              red4(b + 256, v[r][6] + u[r][1].z, v[r][7] + u[r][1].w, v[r][8] + u[r][2].x);
              red4(b + 384, v[r][9] + u[r][2].y, v[r][10] + u[r][2].z, v[r][11] + u[r][2].w);
            }
          bar_arrive(2, 128);
          if (w == 0) STAMPW(98);
        }
      }
      __syncwarp();
      if (lane < 4) mbar_arrive_cl(sb + B_EMPTYO + 8 * (lane >> 1), lane & 1);
    }
    gl += __shfl_xor_sync(0xffffffffu, gl, 1); gl += __shfl_xor_sync(0xffffffffu, gl, 2);
    gl += __shfl_xor_sync(0xffffffffu, gl, 4); gl += __shfl_xor_sync(0xffffffffu, gl, 8);
    if ((lane & 15) == 0) __stcg(prm.s->gate + 128 * rt + 16 * cg + (tid >> 4), gl);
    softmax2(pq, ph0, ph1);
    reg_fence<20>(ph0); reg_fence<20>(ph1);
    STAMPW(24 + warp);
    {
      const int h = lane >> 3, fb = (lane >> 2) & 1;
      const float* src = prm.s->kv + (cg * 2 + (h >> 1)) * 2560 + (warp >> 2) * 512 + (h & 1) * 256 + ((2 * (warp & 3) + fb) * 4 + t) * 4;
      const int j0 = t + 2 * (h & 1), j2 = (h & 1) ? (t == 0 ? 10 : t - 2) : 8 + t;
      const bool has2 = t != ((h & 1) ? 1 : 3);
      const uint32_t dst = sb + OFF_KVB + warp * 128 + (2 * h + fb) * 16 + 4 * h;
      float4 f[3][2];
      if (lane == 0) poll(cnt + (C_KV + cg) * 32, 16 * ep1);
      __syncwarp();
      if (warp == 0) STAMPW(50);
#pragma unroll
      for (int i = 0; i < 3; i++)
        if (i < 2 || warp < 4) { f[i][0] = ld_rlx4(src + i * 1024); f[i][1] = ld_rlx4(src + i * 1024 + 128); }
#pragma unroll
      for (int i = 0; i < 3; i++)
        if (i < 2 || warp < 4) {
          sts32(dst + i * 1024 + j0 * KVB_S, pack(f[i][0].x, f[i][0].y));
          sts32(dst + i * 1024 + (j0 + 4) * KVB_S, pack(f[i][0].z, f[i][1].x));
          if (has2) sts32(dst + i * 1024 + j2 * KVB_S, pack(f[i][1].y, f[i][1].z));
        }
    }
    fence_async();
    bar_sync(1, 256);
    {
      float p[44];
      if (warp == 0) STAMPW(68);
      const uint64_t db = mkdesc(sb + OFF_KVB, 128, KVB_S, 0);
      wg_fence();
#pragma unroll
      for (int s = 0; s < 10; s++) wgmma_rs<88, 1>(p, ph0[2 * s], ph1[2 * s], ph0[2 * s + 1], ph1[2 * s + 1], db + 16 * s, s > 0);
      wg_commit();
      wg_wait<0>();
      reg_fence<44>(p);
      if (warp == 0) STAMPW(69);
      if (lane < 4) mbar_arrive_cl(sb + B_EMPTYO + 16 + 8 * (lane >> 1), lane & 1);
      const float r0 = rcp(p[40] + 1e-6f), r1 = rcp(p[42] + 1e-6f);
      uint32_t* o = (uint32_t*)(prm.s->o + (rt * 8 + cg) * 20480 + (8 * wg + 2 * w) * 128) + lane;
#pragma unroll
      for (int j = 0; j < 10; j++) {
        __stcg(o + j * 512, pack(p[4 * j] * r0, p[4 * j + 1] * r0));
        __stcg(o + j * 512 + 32, pack(p[4 * j + 2] * r1, p[4 * j + 3] * r1));
      }
      __syncwarp();
      if (lane == 0) red_rel(cnt + (C_O + rt) * 32 + cg);
    }
    if (warp == 0) STAMPW(51);
    float p[40];
#pragma unroll
    for (int i = 0; i < 40; i++) p[i] = 0.f;
    reg_fence<40>(p);
    mbar_wait(sb + B_WO, 0);
#pragma unroll 1
    for (int i = 0; i < 8; i++) {
      const int st = i & 3;
      const uint32_t oa = sb + (st < 2 ? OFF_S : OFF_PHI) + (st & 1) * 20480 + wg * 1024;
      const uint32_t wa = OFF_WO + (((i + 3) & 7) - 3) * 10240;
      const uint32_t ta = OFF_WOT + (i >> 2) * 10240 + (i & 3) * 32;
      const uint64_t da = mkdesc(oa, 2048, 128, 0);
      const uint64_t db = mkdesc(sb + wa, ta - wa, 1024, 1);
      mbar_wait(sb + B_FULLO + 8 * st, i >> 2);
      if (warp == 0) STAMPW(52 + i);
      wg_fence();
#pragma unroll
      for (int ks = 0; ks < 5; ks++) wgmma_ss<80, 0, 1>(p, da + 256 * ks, db + 128 * ks, 1);
      wg_commit();
      wg_wait<0>();
      if (i < 6 && lane < 2) mbar_arrive_cl(sb + B_EMPTYO + 8 * st, lane);
    }
    reg_fence<40>(p);
    if (warp == 0) STAMPW(60);
    mbar_wait(sb + B_Y, 0);
    mbar_wait(sb + B_EMPTYO + 8, 0);
    if (warp == 0) STAMPW(61);
    {
      const int r0 = 64 * wg + 16 * w + g;
      const float l0 = __uint_as_float(lds32(sb + OFF_G + r0 * 4)), l1 = __uint_as_float(lds32(sb + OFF_G + r0 * 4 + 32));
      const float g0 = rcp(1.f + ex2(-1.4426950408889634f * l0)), g1 = rcp(1.f + ex2(-1.4426950408889634f * l1));
      const uint32_t ya = sb + OFF_S + ((lane >> 4) * 8 + (lane & 7)) * 256 + (((8 * wg + 2 * w + ((lane >> 3) & 1)) ^ (lane & 7)) * 16);
      const uint32_t ob = sb + OFF_S + 20480 + warp * 2560;
      const uint32_t oa = ob + (lane & 15) * 160 + (lane >> 4) * 16;
#pragma unroll
      for (int j = 0; j < 5; j++) {
        const uint4 y = ldsm4t(ya + j * 4096);
        const float* a = p + 8 * j;
        uint32_t o0 = pack(fmaf(g0, a[0] - blo(y.x), blo(y.x)), fmaf(g0, a[1] - bhi(y.x), bhi(y.x)));
        uint32_t o1 = pack(fmaf(g1, a[2] - blo(y.y), blo(y.y)), fmaf(g1, a[3] - bhi(y.y), bhi(y.y)));
        uint32_t o2 = pack(fmaf(g0, a[4] - blo(y.z), blo(y.z)), fmaf(g0, a[5] - bhi(y.z), bhi(y.z)));
        uint32_t o3 = pack(fmaf(g1, a[6] - blo(y.w), blo(y.w)), fmaf(g1, a[7] - bhi(y.w), bhi(y.w)));
        stsm4(oa + j * 32, o0, o1, o2, o3);
      }
      fence_async();
      __syncwarp();
      if (lane == 0) {
        tma_st2d(&tmOut, ob, 80 * ct3, 128 * rt3 + 16 * warp);
        asm volatile("cp.async.bulk.commit_group;\ncp.async.bulk.wait_group.read 0;" ::: "memory");
      }
    }
    STAMPW(32 + warp);
  } else if (warp < 12) {
    asm volatile("setmaxnreg.dec.sync.aligned.u32 112;");
    const int w = warp & 3, th = tid & 127;
    {
      const int pi = cta * 640 + th;
      uint16_t n_lar = __ldg(prm.lar + pi), n_aim = __ldg(prm.aim + pi), n_cre = __ldg(prm.cre + pi), n_cim = __ldg(prm.cim + pi);
      uint16_t n_ldt = __ldg(prm.ldt + 5 * cta);
      uint16_t m_lar = __ldg(prm.lar + pi + 128), m_aim = __ldg(prm.aim + pi + 128), m_cre = __ldg(prm.cre + pi + 128), m_cim = __ldg(prm.cim + pi + 128);
      uint16_t m_ldt = __ldg(prm.ldt + 5 * cta + 1);
      KPrep k;
      kprep(k, n_lar, n_aim, n_cre, n_cim, n_ldt);
      cl_wait();
      if (w == 0) STAMPW(92);
      const uint32_t ea = sb + ((th & 63) >> 3) * 256 + (th & 7) * 16;
      const int gq = w >> 1;
#pragma unroll 1
      for (int j = 0; j < 5; j++) {
        {
          const uint32_t ba = ea + OFF_KB + gq * 6144;
          sts128(ba, k.B[0], k.B[1], k.B[2], k.B[3]); sts128(ba + 128, k.B[4], k.B[5], k.B[6], k.B[7]);
          sts128(ba + 2048, k.B[8], k.B[9], k.B[10], k.B[11]); sts128(ba + 2048 + 128, k.B[12], k.B[13], k.B[14], k.B[15]);
          sts128(ba + 4096, k.B[16], k.B[17], k.B[18], 0); sts128(ba + 4096 + 128, k.B[19], k.B[20], k.B[21], 0);
          const uint32_t aa = ea + OFF_KA + gq * 8192;
#pragma unroll
          for (int c = 0; c < 4; c++) {
            cf v[8];
            v[0] = k.S[c];
#pragma unroll
            for (int r = 1; r < 8; r++) v[r] = cmul(k.S[c], k.T[r]);
            sts128(aa + c * 2048, pack(v[0].x, v[1].x), pack(v[2].x, v[3].x), pack(v[4].x, v[5].x), pack(v[6].x, v[7].x));
            sts128(aa + c * 2048 + 128, pack(v[0].y, v[1].y), pack(v[2].y, v[3].y), pack(v[4].y, v[5].y), pack(v[6].y, v[7].y));
          }
        }
        fence_async();
        bar_sync(4, 128);
        float kc[24];
        {
          const uint64_t da = mkdesc(sb + OFF_KA, 128, 2048, 0), db = mkdesc(sb + OFF_KB, 128, 2048, 0);
          wg_fence();
#pragma unroll
          for (int s = 0; s < 8; s++) wgmma_ss<48, 1, 1>(kc, da + 16 * s, db + 16 * s, s > 0);
          wg_commit();
        }
        kprep(k, m_lar, m_aim, m_cre, m_cim, m_ldt);
        if (j < 3) {
          const int q = pi + 128 * (j + 2);
          m_lar = __ldg(prm.lar + q); m_aim = __ldg(prm.aim + q); m_cre = __ldg(prm.cre + q); m_cim = __ldg(prm.cim + q);
          m_ldt = __ldg(prm.ldt + 5 * cta + j + 2);
        }
        wg_wait<0>();
        reg_fence<24>(kc);
        bar_sync(6, 192);
        if (j == 4) bar_arrive(7, 160);
        {
          const uint32_t ra = sb + OFF_KR + gq * 2592;
#pragma unroll
          for (int r = 0; r < 2; r++) {
            const int i = 16 * (w & 1) + g + 8 * r;
            float v[6];
#pragma unroll
            for (int c = 0; c < 3; c++) { v[2 * c] = gq ? kc[12 + 4 * c + 2 * r] : kc[4 * c + 2 * r]; v[2 * c + 1] = gq ? kc[13 + 4 * c + 2 * r] : kc[1 + 4 * c + 2 * r]; }
            sts64f(ra + (8 * i + 2 * t) * 4, v[0], v[1]);
            sts64f(ra + (t < 2 ? 256 + 4 * i + 2 * t : 256 + 64 * t + 2 * i) * 4, v[2], v[3]);
            if (t < 2 || (t == 2 && i == 0)) sts32(ra + (512 + 64 * t + i) * 4, __float_as_uint(v[4]));
            if (t < 2) sts32(ra + (544 + 64 * t + i) * 4, __float_as_uint(v[5]));
          }
        }
        bar_arrive(5, 192);
        if (w == 0) STAMPW(85 + j);
      }
    }
#pragma unroll 1
    for (int j = 0; j < 5; j++) {
      const uint32_t ka = sb + OFF_KT + (4 - j) * 4160 + 2 * (2064 - 16 * w - 2 * g + 4 * t);
      float acc[64];
      uint32_t a0[8], a1[8];
#pragma unroll
      for (int i = 0; i < 64; i++) acc[i] = 0.f;
      reg_fence<64>(acc);
      conv_load<0>(ka, a0);
      mbar_wait(sb + B_FULLU + 8 * (j & 1), (j >> 1) & 1);
      if (w == 0) STAMPW(70 + j);
      ConvLoop<0>::run(acc, ka, mkdesc(sb + OFF_U + (j & 1) * 4480, 2240, 128, 0), a0, a1);
      wg_wait<0>();
      reg_fence<64>(acc);
      if (w == 0) STAMPW(75 + j);
      bar_sync(6, 192);
      const uint32_t pa = sb + OFF_P + w * 4096 + ((lane >> 3) & 1) * 2048 + ((lane >> 4) * 8 + (lane & 7)) * 16;
#pragma unroll
      for (int i = 0; i < 8; i++) {
        const float* a = acc + 8 * i;
        stsm4t(pa + i * 256, pack(a[0], a[1]), pack(a[2], a[3]), pack(a[4], a[5]), pack(a[6], a[7]));
      }
      bar_arrive(5, 192);
    }
  } else {
    asm volatile("setmaxnreg.dec.sync.aligned.u32 48;");
    if (warp == 12) {
      if (lane == 0) {
        asm volatile("prefetch.tensormap [%0];" ::"l"(&tmWo) : "memory");
        asm volatile("prefetch.tensormap [%0];" ::"l"(&tmOut) : "memory");
#pragma unroll 1
        for (int kb = 3; kb < 10; kb++) {
          const int s = kb % 3;
          const uint32_t st = sb + OFF_S + ((3 - s) % 3) * STG, bar = sb + B_FULL + 8 * s;
          mbar_wait(sb + B_EMPTY + 8 * s, (kb / 3 - 1) & 1);
          mbar_expect(bar, STG_TX);
          tma2d(st, &tmX, 64 * kb, 128 * rt, bar);
          bulk_ld(st + 31744, prm.gw + 16 * kb, 128, bar);
          tma3d_mc(st + 16384 + rank * 16384, &tmW, 80 * cg, 64 * kb + 32 * rank, 0, bar);
          tma3d_mc(st + 16384 + rank * 16384 + 12288, &tmWt, 80 * cg + 64, 64 * kb + 32 * rank, 0, bar);
        }
        const uint32_t wb = sb + B_WO;
        mbar_wait(sb + B_EMPTY + 8, 0);
        mbar_arrive(sb + B_T);
        mbar_expect(wb, 20480);
        for (int u = 3; u < 5; u++) tma5d(sb + OFF_WO + u * 10240, &tmWo, 80 * ct3, 0, 0, 0, u, wb);
        mbar_wait(sb + B_EMPTY + 16, 0);
        mbar_expect(wb, 30720);
        for (int u = 0; u < 3; u++) tma5d(sb + OFF_WO + u * 10240, &tmWo, 80 * ct3, 0, 0, 0, u, wb);
      }
      __syncwarp();
      const unsigned ep1 = (ld_rlx(cnt + C_DONE * 32) >> 7) + 1;
      bar_sync(2, 128);
      STAMPW(90);
      if (lane == 0) red_rel(cnt + (C_KV + cg) * 32);
      STAMPW(91);
      if (lane == 0) {
        const uint32_t wb = sb + B_WO;
        mbar_wait(sb + B_EMPTYO, 0);
        mbar_expect(wb, 30720);
        for (int u = 5; u < 8; u++) tma5d(sb + OFF_WO + (u - 8) * 10240, &tmWo, 80 * ct3, 0, 0, 0, u, wb);
      }
      __syncwarp();
      {
        unsigned ready = 0;
        int next = 0, n = 0;
        while (next < 8) {
          bool ok = false;
          if (lane < 8 && !((ready >> lane) & 1)) ok = (int)(ld_acq(cnt + (C_O + rt3) * 32 + lane) - 8 * ep1) >= 0;
          ready |= __ballot_sync(0xffffffffu, ok);
          while (next < 8 && ((ready >> next) & 1)) {
            if (lane == next) {
              const int st = next & 3;
              const uint32_t oa = sb + (st < 2 ? OFF_S : OFF_PHI) + (st & 1) * 20480;
              mbar_wait(sb + B_EMPTYO + 8 * st, next >> 2);
              fence_async_g();
              mbar_expect(sb + B_FULLO + 8 * st, 20480);
              bulk_ld_mc(oa + rank * 10240, prm.s->o + (rt3 * 8 + next) * 20480 + rank * 10240, 10240, sb + B_FULLO + 8 * st);
            }
            __syncwarp();
            next++;
          }
          if (++n > SPIN_MAX) __trap();
        }
      }
      if (lane == 0) {
        poll(cnt + (C_Y + ct3) * 32, 32 * ep1);
        mbar_wait(sb + B_EMPTYO, 0);
        fence_async_g();
        mbar_expect(sb + B_Y, 20480 + 512);
        bulk_ld(sb + OFF_S, prm.s->y + (rt3 * 640 + 80 * ct3) * 256, 20480, sb + B_Y);
        bulk_ld(sb + OFF_G, prm.s->gate + rt3 * 128, 512, sb + B_Y);
        red_rlx(cnt + C_DONE * 32);
      }
    } else if (warp == 13) {
      const unsigned ep1 = (ld_rlx(cnt + C_DONE * 32) >> 7) + 1;
      {
        float4* z = (float4*)prm.s->kv + cg * 1280 + rt * 80;
        z[lane] = make_float4(0.f, 0.f, 0.f, 0.f); z[lane + 32] = make_float4(0.f, 0.f, 0.f, 0.f);
        if (lane < 16) z[lane + 64] = make_float4(0.f, 0.f, 0.f, 0.f);
      }
      cl_wait();
      const int trow = 16 * ((lane & 7) >> 1) + 4 * (lane >> 3) + (lane & 1);
      unsigned char* dst = prm.s->xT + (80 * cg + g) * 4096 + (127 - 8 * rt - t) * 16;
      mbar_wait(sb + B_XS, 0);
      STAMPW(93);
#pragma unroll 2
      for (int c = 0; c < 10; c++) {
        uint4 v[4];
#pragma unroll
        for (int i = 0; i < 4; i++) v[i] = ldsm4t(sb + OFF_XS + (trow + 64 * (i & 1) + 2 * (i >> 1)) * 160 + c * 16);
#pragma unroll
        for (int i = 0; i < 4; i++) __stcg((uint4*)(dst + c * 32768 + (i >> 1) * 2048 - (i & 1) * 64), v[i]);
      }
      bar_arrive(8, 96);
      __syncwarp();
      if (lane == 0) red_rel(cnt + (C_X + cg) * 32);
      STAMPW(94);
#pragma unroll
      for (int i = 0; i < 2; i++)
        if ((lane & 15) < 12) sts128(sb + OFF_U + (2 * i + (lane >> 4)) * 2240 + 2048 + (lane & 15) * 16, 0, 0, 0, 0);
      fence_async();
      __syncwarp();
      if (lane == 0) {
        poll(cnt + (C_X + (cta >> 4)) * 32, 16 * ep1);
        fence_async_g();
        for (int j = 0; j < 2; j++) {
          const uint32_t bar = sb + B_FULLU + 8 * j, ub = sb + OFF_U + j * 4480;
          const unsigned char* src = prm.s->xT + (5 * cta + j) * 4096;
          mbar_expect(bar, 4096);
          bulk_ld(ub, src, 2048, bar);
          bulk_ld(ub + 2240, src + 2048, 2048, bar);
        }
        poll(cnt + (C_X + cg) * 32, 16 * ep1);
      }
      STAMPW(95);
      bar_sync(7, 160);
#pragma unroll 8
      for (int i = 0; i < 56; i++) sts128(sb + OFF_KVB + (i * 32 + lane) * 16, 0, 0, 0, 0);
      fence_async();
      __syncwarp();
      if (lane == 0) mbar_arrive(sb + B_Z);
      STAMPW(96);
      mbar_wait(sb + B_T, 0);
      {
        const int c = lane & 1, rr = lane >> 1;
        const uint16_t* src = prm.wo + (20 * ((rr >> 1) & 3) + 2 * (rr >> 3) + (rr & 1)) * 640 + 80 * ct3 + 64 + 8 * c;
#pragma unroll
        for (int q = 0; q < 4; q++) {
          const uint32_t d = sb + OFF_WOT + rr * 128 + (((2 * q + c) ^ (rr & 7)) * 16);
#pragma unroll
          for (int i = 0; i < 10; i++)
            asm volatile("cp.async.cg.shared.global [%0], [%1], 16;" ::"r"(d + (i / 5) * 10240 + (i % 5) * 2048), "l"(src + (80 * (q + 4 * (i / 5)) + 4 * (i % 5)) * 640) : "memory");
        }
      }
      asm volatile("cp.async.wait_all;" ::: "memory");
      fence_async();
      __syncwarp();
      if (lane == 0) mbar_arrive(sb + B_WO);
      STAMPW(97);
    } else {
      const int t64 = tid & 63;
      bar_arrive(6, 192);
      cl_wait();
#pragma unroll 1
      for (int j = 0; j < 5; j++) {
        const float dskip = bf2f(__ldg(prm.dsk + 5 * cta + j));
        bar_sync(5, 192);
#pragma unroll
        for (int i = 0; i < 3; i++) {
          const int idx = t64 + 64 * i;
          if (idx < 161) {
            const float4 a = lds128f(sb + OFF_KR + idx * 16), b = lds128f(sb + OFF_KR + 2592 + idx * 16);
            sts64(sb + OFF_KV16 + idx * 8, pack(a.x + b.x + (idx == 0 ? dskip : 0.f), a.y + b.y), pack(a.z + b.z, a.w + b.w));
          }
        }
        if (j == 2) bar_sync(8, 96); else bar_sync(3, 64);
        const uint32_t kt = sb + OFF_KT + (4 - j) * 4160, kv = sb + OFF_KV16;
        const uint32_t dst = kt + 2 * (2064 - 16 * t64 - 16);
        expand16<3>(kv, 512 + 2 * t64, dst - 2048);
        if (t64 >= 32) expand16<2>(kv, 384 + 4 * (t64 - 32), dst);
        else if (t64 >= 16) expand16<1>(kv, 256 + 8 * (t64 - 16), dst);
        else expand16<0>(kv, 16 * t64, dst);
        if (t64 == 63) {
          sts128(kt + 2 * 2064, lds16(kv), 0, 0, 0);
          sts128(kt + 2 * 2064 + 16, 0, 0, 0, 0);
        }
        bar_arrive(6, 192);
      }
#pragma unroll 1
      for (int j = 0; j < 5; j++) {
        const int ch = 5 * cta + j;
        bar_sync(5, 192);
        if (j < 3 && t64 == 0) {
          const uint32_t bar = sb + B_FULLU + 8 * (j & 1), ub = sb + OFF_U + (j & 1) * 4480;
          const unsigned char* src = prm.s->xT + (ch + 2) * 4096;
          fence_async_g();
          mbar_expect(bar, 4096);
          bulk_ld(ub, src, 2048, bar);
          bulk_ld(ub + 2240, src + 2048, 2048, bar);
        }
#pragma unroll 1
        for (int it = 0; it < 2; it++) {
          const int th = t64 + 64 * it;
          uint4 e[4], o[4];
#pragma unroll
          for (int ww = 0; ww < 4; ww++) {
            const uint32_t pa = sb + OFF_P + ww * 4096 + (127 - th + ww) * 16, za = sb + OFF_U + 2048;
            e[ww] = lds128(th >= ww ? pa : za); o[ww] = lds128(th >= ww ? pa + 2048 : za);
          }
#define SUM4(f, a, c) ((f(a[0].c) + f(a[1].c)) + (f(a[2].c) + f(a[3].c)))
          unsigned char* yb = prm.s->y + ((th >> 3) * 640 + ch) * 256;
          const int c0 = 2 * (th & 7), sw = ch & 7;
          __stcg((uint4*)(yb + ((c0 ^ sw) * 16)), make_uint4(pack(SUM4(blo, e, x), SUM4(blo, o, x)), pack(SUM4(bhi, e, x), SUM4(bhi, o, x)),
                                                             pack(SUM4(blo, e, y), SUM4(blo, o, y)), pack(SUM4(bhi, e, y), SUM4(bhi, o, y))));
          __stcg((uint4*)(yb + (((c0 + 1) ^ sw) * 16)), make_uint4(pack(SUM4(blo, e, z), SUM4(blo, o, z)), pack(SUM4(bhi, e, z), SUM4(bhi, o, z)),
                                                                   pack(SUM4(blo, e, w), SUM4(blo, o, w)), pack(SUM4(bhi, e, w), SUM4(bhi, o, w))));
        }
        if (j < 4) bar_arrive(6, 192);
        if (warp == 14) STAMPW(80 + j);
      }
      __syncwarp();
      if (lane == 0) red_rel(cnt + (C_Y + (cta >> 4)) * 32 );
    }
  }
}

typedef CUresult (*EncFn)(CUtensorMap*, CUtensorMapDataType, cuuint32_t, void*, const cuuint64_t*, const cuuint64_t*, const cuuint32_t*,
                          const cuuint32_t*, CUtensorMapInterleave, CUtensorMapSwizzle, CUtensorMapL2promotion, CUtensorMapFloatOOBfill);
int enc(EncFn fn, CUtensorMap* m, void* p, int rank, const cuuint64_t* gd, const cuuint64_t* gs, const cuuint32_t* bd, CUtensorMapSwizzle sw) {
  const cuuint32_t es[5] = {1, 1, 1, 1, 1};
  return (int)fn(m, CU_TENSOR_MAP_DATA_TYPE_BFLOAT16, rank, p, gd, gs, bd, es, CU_TENSOR_MAP_INTERLEAVE_NONE, sw,
                 CU_TENSOR_MAP_L2_PROMOTION_L2_128B, CU_TENSOR_MAP_FLOAT_OOB_FILL_NONE);
}
int g_enc_err = 0;
}

extern "C" void kernel_launch(void* const* d_in, const int* in_sizes, int n_in, void* d_out, int out_size) {
  static EncFn fn = nullptr;
  static Scratch* scr = nullptr;
  if (!fn) {
    void* p = nullptr;
    cudaDriverEntryPointQueryResult qr;
    cudaGetDriverEntryPoint("cuTensorMapEncodeTiled", &p, cudaEnableDefault, &qr);
    fn = (EncFn)p;
    cudaGetSymbolAddress((void**)&scr, g_s);
    cudaFuncSetAttribute(fused_kernel, cudaFuncAttributeMaxDynamicSharedMemorySize, SMEM_BYTES);
  }
  CUtensorMap mX, mW, mWt, mXs, mWo, mOut;
  int e = 0;
  { cuuint64_t gd[2] = {640, 2048}, gs[1] = {1280}; cuuint32_t bd[2] = {64, 128}; e |= enc(fn, &mX, d_in[0], 2, gd, gs, bd, CU_TENSOR_MAP_SWIZZLE_128B); }
  { cuuint64_t gd[3] = {640, 640, 3}, gs[2] = {3840, 1280}; cuuint32_t bd[3] = {64, 32, 3}; e |= enc(fn, &mW, d_in[1], 3, gd, gs, bd, CU_TENSOR_MAP_SWIZZLE_128B) << 4; }
  { cuuint64_t gd[3] = {640, 640, 3}, gs[2] = {3840, 1280}; cuuint32_t bd[3] = {16, 32, 3}; e |= enc(fn, &mWt, d_in[1], 3, gd, gs, bd, CU_TENSOR_MAP_SWIZZLE_32B) << 8; }
  { cuuint64_t gd[5] = {640, 2, 4, 10, 8}, gs[4] = {1280, 25600, 2560, 102400}; cuuint32_t bd[5] = {64, 2, 4, 10, 1}; e |= enc(fn, &mWo, d_in[3], 5, gd, gs, bd, CU_TENSOR_MAP_SWIZZLE_128B) << 12; }
  { cuuint64_t gd[2] = {640, 2048}, gs[1] = {1280}; cuuint32_t bd[2] = {80, 128}; e |= enc(fn, &mXs, d_in[0], 2, gd, gs, bd, CU_TENSOR_MAP_SWIZZLE_NONE) << 16; }
  { cuuint64_t gd[2] = {640, 2048}, gs[1] = {1280}; cuuint32_t bd[2] = {80, 16}; e |= enc(fn, &mOut, d_out, 2, gd, gs, bd, CU_TENSOR_MAP_SWIZZLE_NONE) << 20; }
  g_enc_err = e;
  if (e) return;
  Params prm;
  prm.s = scr; prm.wo = (const uint16_t*)d_in[3]; prm.lar = (const uint16_t*)d_in[5]; prm.aim = (const uint16_t*)d_in[6];
  prm.cre = (const uint16_t*)d_in[7]; prm.cim = (const uint16_t*)d_in[8]; prm.ldt = (const uint16_t*)d_in[9]; prm.dsk = (const uint16_t*)d_in[10];
  prm.wphi = (const uint32_t*)d_in[2]; prm.gw = (const uint2*)d_in[11];
  prm.x = (const unsigned char*)d_in[0]; prm.w = (const unsigned char*)d_in[1];
  fused_kernel<<<128, 512, SMEM_BYTES, cudaStreamPerThread>>>(prm, mX, mW, mWt, mXs, mWo, mOut);
}
```

```cpp
#include <cuda_runtime.h>
#include <cuda_bf16.h>
#include <cuda.h>
#include <stdint.h>

template<int N, int TA, int TB> __device__ __forceinline__ void wgmma_ss(float* d, uint64_t da, uint64_t db, int sd);
template<int N, int TB> __device__ __forceinline__ void wgmma_rs(float* d, uint32_t a0, uint32_t a1, uint32_t a2, uint32_t a3, uint64_t db, int sd);
template<> __device__ __forceinline__ void wgmma_ss<192,0,1>(float* d, uint64_t da, uint64_t db, int sd) {
  asm volatile("{\n.reg .pred p;\nsetp.ne.b32 p, %98, 0;\n"
  "wgmma.mma_async.sync.aligned.m64n192k16.f32.bf16.bf16 {%0,%1,%2,%3,%4,%5,%6,%7,%8,%9,%10,%11,%12,%13,%14,%15,%16,%17,%18,%19,%20,%21,%22,%23,%24,%25,%26,%27,%28,%29,%30,%31,%32,%33,%34,%35,%36,%37,%38,%39,%40,%41,%42,%43,%44,%45,%46,%47,%48,%49,%50,%51,%52,%53,%54,%55,%56,%57,%58,%59,%60,%61,%62,%63,%64,%65,%66,%67,%68,%69,%70,%71,%72,%73,%74,%75,%76,%77,%78,%79,%80,%81,%82,%83,%84,%85,%86,%87,%88,%89,%90,%91,%92,%93,%94,%95}, %96, %97, p, 1, 1, 0, 1;\n}\n"
  : "+f"(d[0]),"+f"(d[1]),"+f"(d[2]),"+f"(d[3]),"+f"(d[4]),"+f"(d[5]),"+f"(d[6]),"+f"(d[7]),"+f"(d[8]),"+f"(d[9]),"+f"(d[10]),"+f"(d[11]),"+f"(d[12]),"+f"(d[13]),"+f"(d[14]),"+f"(d[15]),"+f"(d[16]),"+f"(d[17]),"+f"(d[18]),"+f"(d[19]),"+f"(d[20]),"+f"(d[21]),"+f"(d[22]),"+f"(d[23]),"+f"(d[24]),"+f"(d[25]),"+f"(d[26]),"+f"(d[27]),"+f"(d[28]),"+f"(d[29]),"+f"(d[30]),"+f"(d[31]),"+f"(d[32]),"+f"(d[33]),"+f"(d[34]),"+f"(d[35]),"+f"(d[36]),"+f"(d[37]),"+f"(d[38]),"+f"(d[39]),"+f"(d[40]),"+f"(d[41]),"+f"(d[42]),"+f"(d[43]),"+f"(d[44]),"+f"(d[45]),"+f"(d[46]),"+f"(d[47]),"+f"(d[48]),"+f"(d[49]),"+f"(d[50]),"+f"(d[51]),"+f"(d[52]),"+f"(d[53]),"+f"(d[54]),"+f"(d[55]),"+f"(d[56]),"+f"(d[57]),"+f"(d[58]),"+f"(d[59]),"+f"(d[60]),"+f"(d[61]),"+f"(d[62]),"+f"(d[63]),"+f"(d[64]),"+f"(d[65]),"+f"(d[66]),"+f"(d[67]),"+f"(d[68]),"+f"(d[69]),"+f"(d[70]),"+f"(d[71]),"+f"(d[72]),"+f"(d[73]),"+f"(d[74]),"+f"(d[75]),"+f"(d[76]),"+f"(d[77]),"+f"(d[78]),"+f"(d[79]),"+f"(d[80]),"+f"(d[81]),"+f"(d[82]),"+f"(d[83]),"+f"(d[84]),"+f"(d[85]),"+f"(d[86]),"+f"(d[87]),"+f"(d[88]),"+f"(d[89]),"+f"(d[90]),"+f"(d[91]),"+f"(d[92]),"+f"(d[93]),"+f"(d[94]),"+f"(d[95]) : "l"(da), "l"(db), "r"(sd));
}
template<> __device__ __forceinline__ void wgmma_ss<48,0,1>(float* d, uint64_t da, uint64_t db, int sd) {
  asm volatile("{\n.reg .pred p;\nsetp.ne.b32 p, %26, 0;\n"
  "wgmma.mma_async.sync.aligned.m64n48k16.f32.bf16.bf16 {%0,%1,%2,%3,%4,%5,%6,%7,%8,%9,%10,%11,%12,%13,%14,%15,%16,%17,%18,%19,%20,%21,%22,%23}, %24, %25, p, 1, 1, 0, 1;\n}\n"
  : "+f"(d[0]),"+f"(d[1]),"+f"(d[2]),"+f"(d[3]),"+f"(d[4]),"+f"(d[5]),"+f"(d[6]),"+f"(d[7]),"+f"(d[8]),"+f"(d[9]),"+f"(d[10]),"+f"(d[11]),"+f"(d[12]),"+f"(d[13]),"+f"(d[14]),"+f"(d[15]),"+f"(d[16]),"+f"(d[17]),"+f"(d[18]),"+f"(d[19]),"+f"(d[20]),"+f"(d[21]),"+f"(d[22]),"+f"(d[23]) : "l"(da), "l"(db), "r"(sd));
}
template<> __device__ __forceinline__ void wgmma_ss<48,1,1>(float* d, uint64_t da, uint64_t db, int sd) {
  asm volatile("{\n.reg .pred p;\nsetp.ne.b32 p, %26, 0;\n"
  "wgmma.mma_async.sync.aligned.m64n48k16.f32.bf16.bf16 {%0,%1,%2,%3,%4,%5,%6,%7,%8,%9,%10,%11,%12,%13,%14,%15,%16,%17,%18,%19,%20,%21,%22,%23}, %24, %25, p, 1, 1, 1, 1;\n}\n"
  : "+f"(d[0]),"+f"(d[1]),"+f"(d[2]),"+f"(d[3]),"+f"(d[4]),"+f"(d[5]),"+f"(d[6]),"+f"(d[7]),"+f"(d[8]),"+f"(d[9]),"+f"(d[10]),"+f"(d[11]),"+f"(d[12]),"+f"(d[13]),"+f"(d[14]),"+f"(d[15]),"+f"(d[16]),"+f"(d[17]),"+f"(d[18]),"+f"(d[19]),"+f"(d[20]),"+f"(d[21]),"+f"(d[22]),"+f"(d[23]) : "l"(da), "l"(db), "r"(sd));
}
template<> __device__ __forceinline__ void wgmma_rs<80,1>(float* d, uint32_t a0, uint32_t a1, uint32_t a2, uint32_t a3, uint64_t db, int sd) {
  asm volatile("{\n.reg .pred p;\nsetp.ne.b32 p, %45, 0;\n"
  "wgmma.mma_async.sync.aligned.m64n80k16.f32.bf16.bf16 {%0,%1,%2,%3,%4,%5,%6,%7,%8,%9,%10,%11,%12,%13,%14,%15,%16,%17,%18,%19,%20,%21,%22,%23,%24,%25,%26,%27,%28,%29,%30,%31,%32,%33,%34,%35,%36,%37,%38,%39}, {%40,%41,%42,%43}, %44, p, 1, 1, 1;\n}\n"
  : "+f"(d[0]),"+f"(d[1]),"+f"(d[2]),"+f"(d[3]),"+f"(d[4]),"+f"(d[5]),"+f"(d[6]),"+f"(d[7]),"+f"(d[8]),"+f"(d[9]),"+f"(d[10]),"+f"(d[11]),"+f"(d[12]),"+f"(d[13]),"+f"(d[14]),"+f"(d[15]),"+f"(d[16]),"+f"(d[17]),"+f"(d[18]),"+f"(d[19]),"+f"(d[20]),"+f"(d[21]),"+f"(d[22]),"+f"(d[23]),"+f"(d[24]),"+f"(d[25]),"+f"(d[26]),"+f"(d[27]),"+f"(d[28]),"+f"(d[29]),"+f"(d[30]),"+f"(d[31]),"+f"(d[32]),"+f"(d[33]),"+f"(d[34]),"+f"(d[35]),"+f"(d[36]),"+f"(d[37]),"+f"(d[38]),"+f"(d[39]) : "r"(a0), "r"(a1), "r"(a2), "r"(a3), "l"(db), "r"(sd));
}
template<> __device__ __forceinline__ void wgmma_ss<32,1,1>(float* d, uint64_t da, uint64_t db, int sd) {
  asm volatile("{\n.reg .pred p;\nsetp.ne.b32 p, %18, 0;\n"
  "wgmma.mma_async.sync.aligned.m64n32k16.f32.bf16.bf16 {%0,%1,%2,%3,%4,%5,%6,%7,%8,%9,%10,%11,%12,%13,%14,%15}, %16, %17, p, 1, 1, 1, 1;\n}\n"
  : "+f"(d[0]),"+f"(d[1]),"+f"(d[2]),"+f"(d[3]),"+f"(d[4]),"+f"(d[5]),"+f"(d[6]),"+f"(d[7]),"+f"(d[8]),"+f"(d[9]),"+f"(d[10]),"+f"(d[11]),"+f"(d[12]),"+f"(d[13]),"+f"(d[14]),"+f"(d[15]) : "l"(da), "l"(db), "r"(sd));
}
template<> __device__ __forceinline__ void wgmma_rs<88,1>(float* d, uint32_t a0, uint32_t a1, uint32_t a2, uint32_t a3, uint64_t db, int sd) {
  asm volatile("{\n.reg .pred p;\nsetp.ne.b32 p, %49, 0;\n"
  "wgmma.mma_async.sync.aligned.m64n88k16.f32.bf16.bf16 {%0,%1,%2,%3,%4,%5,%6,%7,%8,%9,%10,%11,%12,%13,%14,%15,%16,%17,%18,%19,%20,%21,%22,%23,%24,%25,%26,%27,%28,%29,%30,%31,%32,%33,%34,%35,%36,%37,%38,%39,%40,%41,%42,%43}, {%44,%45,%46,%47}, %48, p, 1, 1, 1;\n}\n"
  : "+f"(d[0]),"+f"(d[1]),"+f"(d[2]),"+f"(d[3]),"+f"(d[4]),"+f"(d[5]),"+f"(d[6]),"+f"(d[7]),"+f"(d[8]),"+f"(d[9]),"+f"(d[10]),"+f"(d[11]),"+f"(d[12]),"+f"(d[13]),"+f"(d[14]),"+f"(d[15]),"+f"(d[16]),"+f"(d[17]),"+f"(d[18]),"+f"(d[19]),"+f"(d[20]),"+f"(d[21]),"+f"(d[22]),"+f"(d[23]),"+f"(d[24]),"+f"(d[25]),"+f"(d[26]),"+f"(d[27]),"+f"(d[28]),"+f"(d[29]),"+f"(d[30]),"+f"(d[31]),"+f"(d[32]),"+f"(d[33]),"+f"(d[34]),"+f"(d[35]),"+f"(d[36]),"+f"(d[37]),"+f"(d[38]),"+f"(d[39]),"+f"(d[40]),"+f"(d[41]),"+f"(d[42]),"+f"(d[43]) : "r"(a0), "r"(a1), "r"(a2), "r"(a3), "l"(db), "r"(sd));
}
template<> __device__ __forceinline__ void wgmma_ss<80,0,1>(float* d, uint64_t da, uint64_t db, int sd) {
  asm volatile("{\n.reg .pred p;\nsetp.ne.b32 p, %42, 0;\n"
  "wgmma.mma_async.sync.aligned.m64n80k16.f32.bf16.bf16 {%0,%1,%2,%3,%4,%5,%6,%7,%8,%9,%10,%11,%12,%13,%14,%15,%16,%17,%18,%19,%20,%21,%22,%23,%24,%25,%26,%27,%28,%29,%30,%31,%32,%33,%34,%35,%36,%37,%38,%39}, %40, %41, p, 1, 1, 0, 1;\n}\n"
  : "+f"(d[0]),"+f"(d[1]),"+f"(d[2]),"+f"(d[3]),"+f"(d[4]),"+f"(d[5]),"+f"(d[6]),"+f"(d[7]),"+f"(d[8]),"+f"(d[9]),"+f"(d[10]),"+f"(d[11]),"+f"(d[12]),"+f"(d[13]),"+f"(d[14]),"+f"(d[15]),"+f"(d[16]),"+f"(d[17]),"+f"(d[18]),"+f"(d[19]),"+f"(d[20]),"+f"(d[21]),"+f"(d[22]),"+f"(d[23]),"+f"(d[24]),"+f"(d[25]),"+f"(d[26]),"+f"(d[27]),"+f"(d[28]),"+f"(d[29]),"+f"(d[30]),"+f"(d[31]),"+f"(d[32]),"+f"(d[33]),"+f"(d[34]),"+f"(d[35]),"+f"(d[36]),"+f"(d[37]),"+f"(d[38]),"+f"(d[39]) : "l"(da), "l"(db), "r"(sd));
}
template<> __device__ __forceinline__ void wgmma_rs<16,0>(float* d, uint32_t a0, uint32_t a1, uint32_t a2, uint32_t a3, uint64_t db, int sd) {
  asm volatile("{\n.reg .pred p;\nsetp.ne.b32 p, %13, 0;\n"
  "wgmma.mma_async.sync.aligned.m64n16k16.f32.bf16.bf16 {%0,%1,%2,%3,%4,%5,%6,%7}, {%8,%9,%10,%11}, %12, p, 1, 1, 0;\n}\n"
  : "+f"(d[0]),"+f"(d[1]),"+f"(d[2]),"+f"(d[3]),"+f"(d[4]),"+f"(d[5]),"+f"(d[6]),"+f"(d[7]) : "r"(a0), "r"(a1), "r"(a2), "r"(a3), "l"(db), "r"(sd));
}
template<> __device__ __forceinline__ void wgmma_rs<32,0>(float* d, uint32_t a0, uint32_t a1, uint32_t a2, uint32_t a3, uint64_t db, int sd) {
  asm volatile("{\n.reg .pred p;\nsetp.ne.b32 p, %21, 0;\n"
  "wgmma.mma_async.sync.aligned.m64n32k16.f32.bf16.bf16 {%0,%1,%2,%3,%4,%5,%6,%7,%8,%9,%10,%11,%12,%13,%14,%15}, {%16,%17,%18,%19}, %20, p, 1, 1, 0;\n}\n"
  : "+f"(d[0]),"+f"(d[1]),"+f"(d[2]),"+f"(d[3]),"+f"(d[4]),"+f"(d[5]),"+f"(d[6]),"+f"(d[7]),"+f"(d[8]),"+f"(d[9]),"+f"(d[10]),"+f"(d[11]),"+f"(d[12]),"+f"(d[13]),"+f"(d[14]),"+f"(d[15]) : "r"(a0), "r"(a1), "r"(a2), "r"(a3), "l"(db), "r"(sd));
}
template<> __device__ __forceinline__ void wgmma_rs<48,0>(float* d, uint32_t a0, uint32_t a1, uint32_t a2, uint32_t a3, uint64_t db, int sd) {
  asm volatile("{\n.reg .pred p;\nsetp.ne.b32 p, %29, 0;\n"
  "wgmma.mma_async.sync.aligned.m64n48k16.f32.bf16.bf16 {%0,%1,%2,%3,%4,%5,%6,%7,%8,%9,%10,%11,%12,%13,%14,%15,%16,%17,%18,%19,%20,%21,%22,%23}, {%24,%25,%26,%27}, %28, p, 1, 1, 0;\n}\n"
  : "+f"(d[0]),"+f"(d[1]),"+f"(d[2]),"+f"(d[3]),"+f"(d[4]),"+f"(d[5]),"+f"(d[6]),"+f"(d[7]),"+f"(d[8]),"+f"(d[9]),"+f"(d[10]),"+f"(d[11]),"+f"(d[12]),"+f"(d[13]),"+f"(d[14]),"+f"(d[15]),"+f"(d[16]),"+f"(d[17]),"+f"(d[18]),"+f"(d[19]),"+f"(d[20]),"+f"(d[21]),"+f"(d[22]),"+f"(d[23]) : "r"(a0), "r"(a1), "r"(a2), "r"(a3), "l"(db), "r"(sd));
}
template<> __device__ __forceinline__ void wgmma_rs<64,0>(float* d, uint32_t a0, uint32_t a1, uint32_t a2, uint32_t a3, uint64_t db, int sd) {
  asm volatile("{\n.reg .pred p;\nsetp.ne.b32 p, %37, 0;\n"
  "wgmma.mma_async.sync.aligned.m64n64k16.f32.bf16.bf16 {%0,%1,%2,%3,%4,%5,%6,%7,%8,%9,%10,%11,%12,%13,%14,%15,%16,%17,%18,%19,%20,%21,%22,%23,%24,%25,%26,%27,%28,%29,%30,%31}, {%32,%33,%34,%35}, %36, p, 1, 1, 0;\n}\n"
  : "+f"(d[0]),"+f"(d[1]),"+f"(d[2]),"+f"(d[3]),"+f"(d[4]),"+f"(d[5]),"+f"(d[6]),"+f"(d[7]),"+f"(d[8]),"+f"(d[9]),"+f"(d[10]),"+f"(d[11]),"+f"(d[12]),"+f"(d[13]),"+f"(d[14]),"+f"(d[15]),"+f"(d[16]),"+f"(d[17]),"+f"(d[18]),"+f"(d[19]),"+f"(d[20]),"+f"(d[21]),"+f"(d[22]),"+f"(d[23]),"+f"(d[24]),"+f"(d[25]),"+f"(d[26]),"+f"(d[27]),"+f"(d[28]),"+f"(d[29]),"+f"(d[30]),"+f"(d[31]) : "r"(a0), "r"(a1), "r"(a2), "r"(a3), "l"(db), "r"(sd));
}
template<> __device__ __forceinline__ void wgmma_rs<80,0>(float* d, uint32_t a0, uint32_t a1, uint32_t a2, uint32_t a3, uint64_t db, int sd) {
  asm volatile("{\n.reg .pred p;\nsetp.ne.b32 p, %45, 0;\n"
  "wgmma.mma_async.sync.aligned.m64n80k16.f32.bf16.bf16 {%0,%1,%2,%3,%4,%5,%6,%7,%8,%9,%10,%11,%12,%13,%14,%15,%16,%17,%18,%19,%20,%21,%22,%23,%24,%25,%26,%27,%28,%29,%30,%31,%32,%33,%34,%35,%36,%37,%38,%39}, {%40,%41,%42,%43}, %44, p, 1, 1, 0;\n}\n"
  : "+f"(d[0]),"+f"(d[1]),"+f"(d[2]),"+f"(d[3]),"+f"(d[4]),"+f"(d[5]),"+f"(d[6]),"+f"(d[7]),"+f"(d[8]),"+f"(d[9]),"+f"(d[10]),"+f"(d[11]),"+f"(d[12]),"+f"(d[13]),"+f"(d[14]),"+f"(d[15]),"+f"(d[16]),"+f"(d[17]),"+f"(d[18]),"+f"(d[19]),"+f"(d[20]),"+f"(d[21]),"+f"(d[22]),"+f"(d[23]),"+f"(d[24]),"+f"(d[25]),"+f"(d[26]),"+f"(d[27]),"+f"(d[28]),"+f"(d[29]),"+f"(d[30]),"+f"(d[31]),"+f"(d[32]),"+f"(d[33]),"+f"(d[34]),"+f"(d[35]),"+f"(d[36]),"+f"(d[37]),"+f"(d[38]),"+f"(d[39]) : "r"(a0), "r"(a1), "r"(a2), "r"(a3), "l"(db), "r"(sd));
}
template<> __device__ __forceinline__ void wgmma_rs<96,0>(float* d, uint32_t a0, uint32_t a1, uint32_t a2, uint32_t a3, uint64_t db, int sd) {
  asm volatile("{\n.reg .pred p;\nsetp.ne.b32 p, %53, 0;\n"
  "wgmma.mma_async.sync.aligned.m64n96k16.f32.bf16.bf16 {%0,%1,%2,%3,%4,%5,%6,%7,%8,%9,%10,%11,%12,%13,%14,%15,%16,%17,%18,%19,%20,%21,%22,%23,%24,%25,%26,%27,%28,%29,%30,%31,%32,%33,%34,%35,%36,%37,%38,%39,%40,%41,%42,%43,%44,%45,%46,%47}, {%48,%49,%50,%51}, %52, p, 1, 1, 0;\n}\n"
  : "+f"(d[0]),"+f"(d[1]),"+f"(d[2]),"+f"(d[3]),"+f"(d[4]),"+f"(d[5]),"+f"(d[6]),"+f"(d[7]),"+f"(d[8]),"+f"(d[9]),"+f"(d[10]),"+f"(d[11]),"+f"(d[12]),"+f"(d[13]),"+f"(d[14]),"+f"(d[15]),"+f"(d[16]),"+f"(d[17]),"+f"(d[18]),"+f"(d[19]),"+f"(d[20]),"+f"(d[21]),"+f"(d[22]),"+f"(d[23]),"+f"(d[24]),"+f"(d[25]),"+f"(d[26]),"+f"(d[27]),"+f"(d[28]),"+f"(d[29]),"+f"(d[30]),"+f"(d[31]),"+f"(d[32]),"+f"(d[33]),"+f"(d[34]),"+f"(d[35]),"+f"(d[36]),"+f"(d[37]),"+f"(d[38]),"+f"(d[39]),"+f"(d[40]),"+f"(d[41]),"+f"(d[42]),"+f"(d[43]),"+f"(d[44]),"+f"(d[45]),"+f"(d[46]),"+f"(d[47]) : "r"(a0), "r"(a1), "r"(a2), "r"(a3), "l"(db), "r"(sd));
}
template<> __device__ __forceinline__ void wgmma_rs<112,0>(float* d, uint32_t a0, uint32_t a1, uint32_t a2, uint32_t a3, uint64_t db, int sd) {
  asm volatile("{\n.reg .pred p;\nsetp.ne.b32 p, %61, 0;\n"
  "wgmma.mma_async.sync.aligned.m64n112k16.f32.bf16.bf16 {%0,%1,%2,%3,%4,%5,%6,%7,%8,%9,%10,%11,%12,%13,%14,%15,%16,%17,%18,%19,%20,%21,%22,%23,%24,%25,%26,%27,%28,%29,%30,%31,%32,%33,%34,%35,%36,%37,%38,%39,%40,%41,%42,%43,%44,%45,%46,%47,%48,%49,%50,%51,%52,%53,%54,%55}, {%56,%57,%58,%59}, %60, p, 1, 1, 0;\n}\n"
  : "+f"(d[0]),"+f"(d[1]),"+f"(d[2]),"+f"(d[3]),"+f"(d[4]),"+f"(d[5]),"+f"(d[6]),"+f"(d[7]),"+f"(d[8]),"+f"(d[9]),"+f"(d[10]),"+f"(d[11]),"+f"(d[12]),"+f"(d[13]),"+f"(d[14]),"+f"(d[15]),"+f"(d[16]),"+f"(d[17]),"+f"(d[18]),"+f"(d[19]),"+f"(d[20]),"+f"(d[21]),"+f"(d[22]),"+f"(d[23]),"+f"(d[24]),"+f"(d[25]),"+f"(d[26]),"+f"(d[27]),"+f"(d[28]),"+f"(d[29]),"+f"(d[30]),"+f"(d[31]),"+f"(d[32]),"+f"(d[33]),"+f"(d[34]),"+f"(d[35]),"+f"(d[36]),"+f"(d[37]),"+f"(d[38]),"+f"(d[39]),"+f"(d[40]),"+f"(d[41]),"+f"(d[42]),"+f"(d[43]),"+f"(d[44]),"+f"(d[45]),"+f"(d[46]),"+f"(d[47]),"+f"(d[48]),"+f"(d[49]),"+f"(d[50]),"+f"(d[51]),"+f"(d[52]),"+f"(d[53]),"+f"(d[54]),"+f"(d[55]) : "r"(a0), "r"(a1), "r"(a2), "r"(a3), "l"(db), "r"(sd));
}
template<> __device__ __forceinline__ void wgmma_rs<128,0>(float* d, uint32_t a0, uint32_t a1, uint32_t a2, uint32_t a3, uint64_t db, int sd) {
  asm volatile("{\n.reg .pred p;\nsetp.ne.b32 p, %69, 0;\n"
  "wgmma.mma_async.sync.aligned.m64n128k16.f32.bf16.bf16 {%0,%1,%2,%3,%4,%5,%6,%7,%8,%9,%10,%11,%12,%13,%14,%15,%16,%17,%18,%19,%20,%21,%22,%23,%24,%25,%26,%27,%28,%29,%30,%31,%32,%33,%34,%35,%36,%37,%38,%39,%40,%41,%42,%43,%44,%45,%46,%47,%48,%49,%50,%51,%52,%53,%54,%55,%56,%57,%58,%59,%60,%61,%62,%63}, {%64,%65,%66,%67}, %68, p, 1, 1, 0;\n}\n"
  : "+f"(d[0]),"+f"(d[1]),"+f"(d[2]),"+f"(d[3]),"+f"(d[4]),"+f"(d[5]),"+f"(d[6]),"+f"(d[7]),"+f"(d[8]),"+f"(d[9]),"+f"(d[10]),"+f"(d[11]),"+f"(d[12]),"+f"(d[13]),"+f"(d[14]),"+f"(d[15]),"+f"(d[16]),"+f"(d[17]),"+f"(d[18]),"+f"(d[19]),"+f"(d[20]),"+f"(d[21]),"+f"(d[22]),"+f"(d[23]),"+f"(d[24]),"+f"(d[25]),"+f"(d[26]),"+f"(d[27]),"+f"(d[28]),"+f"(d[29]),"+f"(d[30]),"+f"(d[31]),"+f"(d[32]),"+f"(d[33]),"+f"(d[34]),"+f"(d[35]),"+f"(d[36]),"+f"(d[37]),"+f"(d[38]),"+f"(d[39]),"+f"(d[40]),"+f"(d[41]),"+f"(d[42]),"+f"(d[43]),"+f"(d[44]),"+f"(d[45]),"+f"(d[46]),"+f"(d[47]),"+f"(d[48]),"+f"(d[49]),"+f"(d[50]),"+f"(d[51]),"+f"(d[52]),"+f"(d[53]),"+f"(d[54]),"+f"(d[55]),"+f"(d[56]),"+f"(d[57]),"+f"(d[58]),"+f"(d[59]),"+f"(d[60]),"+f"(d[61]),"+f"(d[62]),"+f"(d[63]) : "r"(a0), "r"(a1), "r"(a2), "r"(a3), "l"(db), "r"(sd));
}

namespace {
typedef __nv_bfloat16 bf16;
constexpr int OFF_S    = 1024;
constexpr int STG      = 49152;
constexpr int STG_TX   = 47104;
constexpr int OFF_PHIK = OFF_S - 128;
constexpr int PHIK_HS  = 10240 + 32;
constexpr int OFF_VB   = OFF_S + 49152;
constexpr int OFF_WO   = OFF_S + 75776;
constexpr int OFF_WOT  = OFF_S + 126976;
constexpr int OFF_PHI  = OFF_S + 147456;
constexpr int OFF_KVB  = OFF_PHI + 12800;
constexpr int KVB_S    = 2592;
constexpr int OFF_KA   = OFF_KVB;
constexpr int OFF_KB   = OFF_KVB + 16384;
constexpr int OFF_U    = OFF_KVB + 28672;
constexpr int OFF_KT   = OFF_U + 8960;
constexpr int OFF_P    = OFF_KT + 16640;
constexpr int OFF_KR   = OFF_P + 4160;
constexpr int OFF_KV16 = OFF_KR + 5184;
constexpr int OFF_G    = 256;
constexpr int OFF_KX   = OFF_S + 40960;
constexpr int SMEM_BYTES = OFF_P + 16384;
static_assert(SMEM_BYTES <= 232448, "smem");
constexpr int B_FULL = 0, B_EMPTY = 24, B_FULLO = 48, B_EMPTYO = 80, B_WO = 112, B_Y = 120, B_FULLU = 128, B_Z = 152, B_T = 160, B_KX = 168;
constexpr int C_X = 0, C_Y = 8, C_KV = 16, C_G = 24, C_O = 40, C_DONE = 56, C_NUM = 64;

struct Scratch {
  unsigned char xT[640 * 4096];
  unsigned char y[16 * 640 * 256];
  unsigned char o[16 * 8 * 20480];
  float kv[8 * 2 * 2560];
  float gate[16 * 128];
  unsigned cnt[C_NUM * 32];
};
__device__ __align__(1024) Scratch g_s;
#define STAMPM(i)
#define STAMP(i)
#define STAMPW(i)

#define KMMA 8
constexpr int SPIN_MAX = 1 << 22;
__device__ __forceinline__ uint32_t smem_u32(const void* p) { return (uint32_t)__cvta_generic_to_shared(p); }
__device__ __forceinline__ void mbar_init(uint32_t bar, int cnt) { asm volatile("mbarrier.init.shared::cta.b64 [%0], %1;" ::"r"(bar), "r"(cnt)); }
__device__ __forceinline__ void mbar_expect(uint32_t bar, int bytes) { asm volatile("mbarrier.arrive.expect_tx.shared::cta.b64 _, [%0], %1;" ::"r"(bar), "r"(bytes) : "memory"); }
__device__ __forceinline__ void mbar_arrive(uint32_t bar) { asm volatile("mbarrier.arrive.shared::cta.b64 _, [%0];" ::"r"(bar) : "memory"); }
__device__ __forceinline__ void mbar_arrive_cl(uint32_t bar, uint32_t cta) {
  asm volatile("{\n.reg .b32 ra;\nmapa.shared::cluster.u32 ra, %0, %1;\nmbarrier.arrive.shared::cluster.b64 _, [ra];\n}\n" ::"r"(bar), "r"(cta) : "memory");
}
__device__ __forceinline__ bool mbar_try(uint32_t bar, int parity) {
  uint32_t ok;
  asm volatile("{\n.reg .pred p;\nmbarrier.try_wait.parity.shared::cta.b64 p, [%1], %2;\nselp.u32 %0, 1, 0, p;\n}\n" : "=r"(ok) : "r"(bar), "r"(parity) : "memory");
  return ok;
}
__device__ __forceinline__ void mbar_wait(uint32_t bar, int parity) {
  int n = 0;
  while (!mbar_try(bar, parity)) { if (++n > SPIN_MAX) __trap(); }
}
__device__ __forceinline__ void mbar_wait_nt(uint32_t bar, int parity) {
  int n = 0;
  while (!mbar_try(bar, parity) && ++n < SPIN_MAX) {}
}
__device__ __forceinline__ unsigned ld_acq(const unsigned* p) { unsigned v; asm volatile("ld.acquire.gpu.global.u32 %0, [%1];" : "=r"(v) : "l"(p) : "memory"); return v; }
__device__ __forceinline__ void poll(const unsigned* p, unsigned target) {
  int n = 0;
  while ((int)(ld_acq(p) - target) < 0) { if (++n > SPIN_MAX) __trap(); }
}
__device__ __forceinline__ void red_rel(unsigned* p) { asm volatile("red.release.gpu.global.add.u32 [%0], 1;" ::"l"(p) : "memory"); }
__device__ __forceinline__ void red_rlx(unsigned* p) { asm volatile("red.relaxed.gpu.global.add.u32 [%0], 1;" ::"l"(p) : "memory"); }
__device__ __forceinline__ void fence_async() { asm volatile("fence.proxy.async.shared::cta;" ::: "memory"); }
__device__ __forceinline__ void fence_async_g() { asm volatile("fence.proxy.async.global;" ::: "memory"); }
__device__ __forceinline__ void bar_sync(int id, int n) { asm volatile("bar.sync %0, %1;" ::"r"(id), "r"(n) : "memory"); }
__device__ __forceinline__ void bar_arrive(int id, int n) { asm volatile("bar.arrive %0, %1;" ::"r"(id), "r"(n) : "memory"); }
__device__ __forceinline__ void wg_fence() { asm volatile("wgmma.fence.sync.aligned;" ::: "memory"); }
__device__ __forceinline__ void wg_commit() { asm volatile("wgmma.commit_group.sync.aligned;" ::: "memory"); }
template <int N> __device__ __forceinline__ void wg_wait() { asm volatile("wgmma.wait_group.sync.aligned %0;" ::"n"(N) : "memory"); }
template <int N> __device__ __forceinline__ void reg_fence(float* d) {
#pragma unroll
  for (int i = 0; i < N; i++) asm volatile("" : "+f"(d[i])::"memory");
}
template <int N> __device__ __forceinline__ void reg_fence(uint32_t* d) {
#pragma unroll
  for (int i = 0; i < N; i++) asm volatile("" : "+r"(d[i])::"memory");
}
__device__ __forceinline__ uint64_t mkdesc(uint32_t addr, uint32_t lbo, uint32_t sbo, uint32_t swz) {
  return (uint64_t)((addr >> 4) & 0x3FFF) | ((uint64_t)(lbo >> 4) << 16) | ((uint64_t)(sbo >> 4) << 32) | ((uint64_t)swz << 62);
}
__device__ __forceinline__ uint32_t pack(float lo, float hi) { uint32_t r; asm("cvt.rn.bf16x2.f32 %0, %1, %2;" : "=r"(r) : "f"(hi), "f"(lo)); return r; }
__device__ __forceinline__ float blo(uint32_t v) { return __uint_as_float(v << 16); }
__device__ __forceinline__ float bhi(uint32_t v) { return __uint_as_float(v & 0xFFFF0000u); }
__device__ __forceinline__ float ex2(float x) { float r; asm("ex2.approx.ftz.f32 %0, %1;" : "=f"(r) : "f"(x)); return r; }
__device__ __forceinline__ float rcp(float x) { float r; asm("rcp.approx.ftz.f32 %0, %1;" : "=f"(r) : "f"(x)); return r; }
__device__ __forceinline__ void sts32(uint32_t a, uint32_t v) { asm volatile("st.shared.u32 [%0], %1;" ::"r"(a), "r"(v) : "memory"); }
__device__ __forceinline__ void sts64f(uint32_t a, float x, float y) { asm volatile("st.shared.v2.f32 [%0], {%1,%2};" ::"r"(a), "f"(x), "f"(y) : "memory"); }
__device__ __forceinline__ void sts128(uint32_t a, uint32_t x, uint32_t y, uint32_t z, uint32_t w) { asm volatile("st.shared.v4.u32 [%0], {%1,%2,%3,%4};" ::"r"(a), "r"(x), "r"(y), "r"(z), "r"(w) : "memory"); }
__device__ __forceinline__ uint32_t lds32(uint32_t a) { uint32_t v; asm volatile("ld.shared.u32 %0, [%1];" : "=r"(v) : "r"(a) : "memory"); return v; }
__device__ __forceinline__ uint32_t lds16(uint32_t a) { uint16_t v; asm volatile("ld.shared.u16 %0, [%1];" : "=h"(v) : "r"(a) : "memory"); return v; }
__device__ __forceinline__ uint4 lds128(uint32_t a) { uint4 v; asm volatile("ld.shared.v4.u32 {%0,%1,%2,%3}, [%4];" : "=r"(v.x), "=r"(v.y), "=r"(v.z), "=r"(v.w) : "r"(a) : "memory"); return v; }
__device__ __forceinline__ float4 lds128f(uint32_t a) { float4 v; asm volatile("ld.shared.v4.f32 {%0,%1,%2,%3}, [%4];" : "=f"(v.x), "=f"(v.y), "=f"(v.z), "=f"(v.w) : "r"(a) : "memory"); return v; }
__device__ __forceinline__ void stsm4(uint32_t a, uint32_t r0, uint32_t r1, uint32_t r2, uint32_t r3) { asm volatile("stmatrix.sync.aligned.m8n8.x4.shared.b16 [%0], {%1,%2,%3,%4};" ::"r"(a), "r"(r0), "r"(r1), "r"(r2), "r"(r3) : "memory"); }
__device__ __forceinline__ void stsm4t(uint32_t a, uint32_t r0, uint32_t r1, uint32_t r2, uint32_t r3) { asm volatile("stmatrix.sync.aligned.m8n8.x4.trans.shared.b16 [%0], {%1,%2,%3,%4};" ::"r"(a), "r"(r0), "r"(r1), "r"(r2), "r"(r3) : "memory"); }
__device__ __forceinline__ uint4 ldsm4t(uint32_t a) { uint4 v; asm volatile("ldmatrix.sync.aligned.m8n8.x4.trans.shared.b16 {%0,%1,%2,%3}, [%4];" : "=r"(v.x), "=r"(v.y), "=r"(v.z), "=r"(v.w) : "r"(a) : "memory"); return v; }
__device__ __forceinline__ void tma2d(uint32_t dst, const CUtensorMap* m, int c0, int c1, uint32_t bar) {
  asm volatile("cp.async.bulk.tensor.2d.shared::cluster.global.mbarrier::complete_tx::bytes [%0], [%1, {%3,%4}], [%2];" ::"r"(dst), "l"(m), "r"(bar), "r"(c0), "r"(c1) : "memory");
}
__device__ __forceinline__ void tma3d(uint32_t dst, const CUtensorMap* m, int c0, int c1, int c2, uint32_t bar) {
  asm volatile("cp.async.bulk.tensor.3d.shared::cluster.global.mbarrier::complete_tx::bytes [%0], [%1, {%3,%4,%5}], [%2];" ::"r"(dst), "l"(m), "r"(bar), "r"(c0), "r"(c1), "r"(c2) : "memory");
}
__device__ __forceinline__ void tma3d_mc(uint32_t dst, const CUtensorMap* m, int c0, int c1, int c2, uint32_t bar) {
  asm volatile("cp.async.bulk.tensor.3d.shared::cluster.global.mbarrier::complete_tx::bytes.multicast::cluster [%0], [%1, {%3,%4,%5}], [%2], %6;" ::"r"(dst), "l"(m), "r"(bar), "r"(c0), "r"(c1), "r"(c2), "h"((uint16_t)3) : "memory");
}
__device__ __forceinline__ void tma5d(uint32_t dst, const CUtensorMap* m, int c0, int c1, int c2, int c3, int c4, uint32_t bar) {
  asm volatile("cp.async.bulk.tensor.5d.shared::cluster.global.mbarrier::complete_tx::bytes [%0], [%1, {%3,%4,%5,%6,%7}], [%2];" ::"r"(dst), "l"(m), "r"(bar), "r"(c0), "r"(c1), "r"(c2), "r"(c3), "r"(c4) : "memory");
}
__device__ __forceinline__ void bulk_ld(uint32_t dst, const void* src, int bytes, uint32_t bar) {
  asm volatile("cp.async.bulk.shared::cluster.global.mbarrier::complete_tx::bytes [%0], [%1], %2, [%3];" ::"r"(dst), "l"(src), "r"(bytes), "r"(bar) : "memory");
}
__device__ __forceinline__ void bulk_ld_mc(uint32_t dst, const void* src, int bytes, uint32_t bar) {
  asm volatile("cp.async.bulk.shared::cluster.global.mbarrier::complete_tx::bytes.multicast::cluster [%0], [%1], %2, [%3], %4;" ::"r"(dst), "l"(src), "r"(bytes), "r"(bar), "h"((uint16_t)3) : "memory");
}
__device__ __forceinline__ void tma_st2d(const CUtensorMap* m, uint32_t src, int c0, int c1) {
  asm volatile("cp.async.bulk.tensor.2d.global.shared::cta.bulk_group [%0, {%2,%3}], [%1];" ::"l"(m), "r"(src), "r"(c0), "r"(c1) : "memory");
}
__device__ __forceinline__ void red4(float* p, float a, float b, float c) { asm volatile("red.relaxed.gpu.global.add.v4.f32 [%0], {%1,%2,%3,%4};" ::"l"(p), "f"(a), "f"(b), "f"(c), "f"(1.f) : "memory"); }
__device__ __forceinline__ float4 ld_rlx4(const float* p) { float4 v; asm volatile("ld.relaxed.gpu.global.v4.f32 {%0,%1,%2,%3}, [%4];" : "=f"(v.x), "=f"(v.y), "=f"(v.z), "=f"(v.w) : "l"(p) : "memory"); return v; }
__device__ __forceinline__ unsigned ld_rlx(const unsigned* p) { unsigned v; asm volatile("ld.relaxed.gpu.global.u32 %0, [%1];" : "=r"(v) : "l"(p) : "memory"); return v; }
__device__ __forceinline__ void sts64(uint32_t a, uint32_t x, uint32_t y) { asm volatile("st.shared.v2.u32 [%0], {%1,%2};" ::"r"(a), "r"(x), "r"(y) : "memory"); }
__device__ __forceinline__ uint32_t mapa(uint32_t a, uint32_t cta) { uint32_t r; asm("mapa.shared::cluster.u32 %0, %1, %2;" : "=r"(r) : "r"(a), "r"(cta)); return r; }
__device__ __forceinline__ void st_async4(uint32_t a, float x, float y, float z, float w, uint32_t bar) {
  asm volatile("st.async.weak.shared::cluster.mbarrier::complete_tx::bytes.v4.f32 [%0], {%1,%2,%3,%4}, [%5];" ::"r"(a), "f"(x), "f"(y), "f"(z), "f"(w), "r"(bar) : "memory");
}
__device__ __forceinline__ void cl_arrive() { asm volatile("barrier.cluster.arrive.relaxed.aligned;" ::: "memory"); }
__device__ __forceinline__ void cl_wait() { asm volatile("barrier.cluster.wait.acquire.aligned;" ::: "memory"); }
__device__ __forceinline__ float bf2f(uint16_t v) { return __uint_as_float((uint32_t)v << 16); }
__device__ __forceinline__ float rbf(float x) { return __bfloat162float(__float2bfloat16_rn(x)); }

__device__ __forceinline__ void softmax2(const float* p, uint32_t* ph0, uint32_t* ph1) {
  constexpr float L = 1.4426950408889634f;
#pragma unroll
  for (int r = 0; r < 2; r++) {
    uint32_t* ph = r ? ph1 : ph0;
    float mx = fmaxf(p[2 * r], p[2 * r + 1]), mn = fminf(p[2 * r], p[2 * r + 1]);
#pragma unroll
    for (int j = 1; j < 10; j++) {
      mx = fmaxf(mx, fmaxf(p[4 * j + 2 * r], p[4 * j + 2 * r + 1]));
      mn = fminf(mn, fminf(p[4 * j + 2 * r], p[4 * j + 2 * r + 1]));
    }
    const float mxl = -mx * L, mnl = mn * L;
    float e[20], s0 = 0.f, s1 = 0.f;
#pragma unroll
    for (int j = 0; j < 10; j++) {
      e[2 * j] = ex2(fmaf(p[4 * j + 2 * r], L, mxl));
      e[2 * j + 1] = ex2(fmaf(p[4 * j + 2 * r + 1], L, mxl));
      s0 += e[2 * j]; s1 += e[2 * j + 1];
    }
    float rs = rcp(s0 + s1);
#pragma unroll
    for (int j = 0; j < 10; j++) ph[j] = pack(e[2 * j] * rs, e[2 * j + 1] * rs);
    s0 = 0.f; s1 = 0.f;
#pragma unroll
    for (int j = 0; j < 10; j++) {
      e[2 * j] = ex2(fmaf(p[4 * j + 2 * r], -L, mnl));
      e[2 * j + 1] = ex2(fmaf(p[4 * j + 2 * r + 1], -L, mnl));
      s0 += e[2 * j]; s1 += e[2 * j + 1];
    }
    rs = rcp(s0 + s1);
#pragma unroll
    for (int j = 0; j < 10; j++) ph[10 + j] = pack(e[2 * j] * rs, e[2 * j + 1] * rs);
  }
}

struct cf { float x, y; };
__device__ __forceinline__ cf cexpp(float a2, float be, float p) {
  float m = ex2(a2 * p), th = be * p;
  return cf{m * __cosf(th), m * __sinf(th)};
}
__device__ __forceinline__ cf cmul(cf a, cf b) { return cf{fmaf(a.x, b.x, -a.y * b.y), fmaf(a.x, b.y, a.y * b.x)}; }

template <int SH> __device__ __forceinline__ void expand16(uint32_t kv, int base, uint32_t dst) {
  constexpr int NV = (16 >> SH) + 1;
  uint32_t v[NV];
#pragma unroll
  for (int i = 0; i < NV; i++) v[i] = (SH == 0 && i == 0) ? 0u : lds16(kv + 2 * (base + i));
  uint32_t w[8];
#pragma unroll
  for (int i = 0; i < 8; i++) {
    int q[2];
#pragma unroll
    for (int h = 0; h < 2; h++) {
      int e = 16 - (2 * i + h);
      int qq = e >> SH, rem = e & ((1 << SH) - 1), half = (1 << SH) >> 1;
      if (SH > 0 && (rem > half || (rem == half && (qq & 1)))) qq++;
      q[h] = qq;
    }
    w[i] = v[q[0]] | (v[q[1]] << 16);
  }
  sts128(dst, w[0], w[1], w[2], w[3]);
  sts128(dst + 16, w[4], w[5], w[6], w[7]);
}

template <int G> __device__ __forceinline__ void conv_load(uint32_t ka, uint32_t* a) {
#pragma unroll
  for (int h = 0; h < 2; h++) {
    const uint32_t ad = ka - 128 * (2 * G + h);
    uint32_t wm = lds32(ad - 4), w0 = lds32(ad), w1 = lds32(ad + 4);
    a[4 * h + 0] = w0; a[4 * h + 1] = __byte_perm(wm, w0, 0x5432);
    a[4 * h + 2] = w1; a[4 * h + 3] = __byte_perm(w0, w1, 0x5432);
  }
  reg_fence<8>(a);
}
template <int G> struct ConvLoop {
  static __device__ __forceinline__ void run(float* acc, uint32_t ka, uint64_t db, uint32_t* cur, uint32_t* nxt) {
    wg_fence();
    wgmma_rs<128 - 16 * (G / 2), 0>(acc, cur[0], cur[1], cur[2], cur[3], db + 8 * G, 1);
    wgmma_rs<128 - 16 * (G / 2), 0>(acc, cur[4], cur[5], cur[6], cur[7], db + 8 * G + 4, 1);
    wg_commit();
    if (G < 15) {
      wg_wait<1>();
      conv_load<G + 1>(ka, nxt);
      ConvLoop<G + 1>::run(acc, ka, db, nxt, cur);
    }
  }
};
template <> struct ConvLoop<16> { static __device__ __forceinline__ void run(float*, uint32_t, uint64_t, uint32_t*, uint32_t*) {} };

struct KPrep { cf T[8], S[4]; uint32_t B[22]; };
__device__ __forceinline__ void kprep(KPrep& k, uint16_t n_lar, uint16_t n_aim, uint16_t n_cre, uint16_t n_cim, uint16_t n_ldt) {
  const float dt = rbf(expf(bf2f(n_ldt)));
  const float a2 = -rbf(expf(bf2f(n_lar))) * dt * 1.4426950408889634f, be = bf2f(n_aim) * dt;
  cf z[8];
  z[1] = cexpp(a2, be, 1.f);
  k.T[1] = cexpp(a2, -be, 8.f);
  const cf z64 = cexpp(a2, -be, 64.f), z256 = cexpp(a2, be, 256.f), z1024 = cexpp(a2, be, 1024.f);
  z[2] = cmul(z[1], z[1]); z[3] = cmul(z[2], z[1]); z[4] = cmul(z[2], z[2]);
  z[5] = cmul(z[4], z[1]); z[6] = cmul(z[4], z[2]); z[7] = cmul(z[4], z[3]);
  k.T[2] = cmul(k.T[1], k.T[1]); k.T[3] = cmul(k.T[2], k.T[1]); k.T[4] = cmul(k.T[2], k.T[2]);
  k.T[5] = cmul(k.T[4], k.T[1]); k.T[6] = cmul(k.T[4], k.T[2]); k.T[7] = cmul(k.T[4], k.T[3]);
  k.S[0] = cf{2.f * (bf2f(n_cre) * dt), -2.f * (bf2f(n_cim) * dt)};
  k.S[1] = cmul(k.S[0], z64); k.S[2] = cmul(k.S[1], z64); k.S[3] = cmul(k.S[2], z64);
  k.B[0] = pack(1.f, z[1].x); k.B[4] = pack(0.f, z[1].y);
#pragma unroll
  for (int i = 1; i < 4; i++) { k.B[i] = pack(z[2 * i].x, z[2 * i + 1].x); k.B[4 + i] = pack(z[2 * i].y, z[2 * i + 1].y); }
  const cf z512 = cmul(z256, z256), z768 = cmul(z512, z256);
  cf a = cmul(z256, z[2]);
  k.B[8] = pack(z256.x, a.x); k.B[12] = pack(z256.y, a.y);
  a = cmul(z256, z[4]);
  cf b = cmul(z256, z[6]);
  k.B[9] = pack(a.x, b.x); k.B[13] = pack(a.y, b.y);
  a = cmul(z512, z[4]);
  k.B[10] = pack(z512.x, a.x); k.B[14] = pack(z512.y, a.y);
  a = cmul(z768, z[4]);
  k.B[11] = pack(z768.x, a.x); k.B[15] = pack(z768.y, a.y);
  a = cmul(z1024, z256);
  k.B[16] = pack(z1024.x, a.x); k.B[19] = pack(z1024.y, a.y);
  a = cmul(z1024, z512); b = cmul(z1024, z768);
  k.B[17] = pack(a.x, b.x); k.B[20] = pack(a.y, b.y);
  a = cmul(z1024, z1024);
  k.B[18] = pack(a.x, 0.f); k.B[21] = pack(a.y, 0.f);
}

struct Params {
  Scratch* s;
  const uint16_t *wo, *lar, *aim, *cre, *cim, *ldt, *dsk;
  const uint32_t* wphi;
  const uint4 *gw, *x;
};

__global__ void __cluster_dims__(2, 1, 1) __launch_bounds__(512, 1)
fused_kernel(const __grid_constant__ Params prm, const __grid_constant__ CUtensorMap tmX, const __grid_constant__ CUtensorMap tmW,
             const __grid_constant__ CUtensorMap tmWt, const __grid_constant__ CUtensorMap tmWo,
             const __grid_constant__ CUtensorMap tmOut) {
  extern __shared__ __align__(1024) unsigned char smem_raw[];
  const uint32_t sb = smem_u32(smem_raw);
  const int tid = threadIdx.x, lane = tid & 31;
  const int warp = __shfl_sync(0xffffffffu, tid >> 5, 0);
  const int g = lane >> 2, t = lane & 3;
  const int cta = blockIdx.x, rank = cta & 1, cl = cta >> 1;
  const int cg = cl & 7, rt = 2 * (cl >> 3) + rank;
  const int rt3 = 2 * (cl >> 3) + (cg & 1), ct3 = (cg & 6) + rank;
  unsigned* const cnt = prm.s->cnt;

  if (warp == 12) {
    if (lane == 0) {
      mbar_init(sb + B_FULL, 1);
      asm volatile("fence.mbarrier_init.release.cluster;" ::: "memory");
    }
    __syncwarp();
    cl_arrive();
    STAMPW(110);
    if (lane == 0) {
      mbar_expect(sb + B_FULL, STG_TX);
      tma2d(sb + OFF_S, &tmX, 0, 128 * rt, sb + B_FULL);
      STAMP(113);
      for (int h = 0; h < 2; h++) {
        tma3d(sb + OFF_S + 16384 + h * 16384, &tmW, 80 * cg, 32 * h, 0, sb + B_FULL);
        tma3d(sb + OFF_S + 16384 + h * 16384 + 12288, &tmWt, 80 * cg + 64, 32 * h, 0, sb + B_FULL);
      }
    }
    __syncwarp();
    STAMPW(111);
  } else if (warp == 13) {
    if (lane == 0) {
      asm volatile("prefetch.tensormap [%0];" ::"l"(&tmW) : "memory");
      asm volatile("prefetch.tensormap [%0];" ::"l"(&tmWt) : "memory");
      mbar_init(sb + B_FULL + 8, 1); mbar_init(sb + B_FULL + 16, 1);
      for (int i = 0; i < 3; i++) mbar_init(sb + B_EMPTY + 8 * i, 16);
      for (int i = 0; i < 4; i++) { mbar_init(sb + B_FULLO + 8 * i, 1); mbar_init(sb + B_EMPTYO + 8 * i, 16); }
      mbar_init(sb + B_WO, 4); mbar_init(sb + B_Y, 1); mbar_init(sb + B_FULLU, 1); mbar_init(sb + B_FULLU + 8, 1);
      mbar_init(sb + B_Z, 1); mbar_init(sb + B_T, 1); mbar_init(sb + B_KX, 1);
      asm volatile("fence.mbarrier_init.release.cluster;" ::: "memory");
    }
    __syncwarp();
    cl_arrive();
    cl_wait();
    STAMPW(112);
    if (lane == 0) {
      for (int kb = 1; kb < 3; kb++) {
        const uint32_t st = sb + OFF_S + (3 - kb) * STG, bar = sb + B_FULL + 8 * kb;
        mbar_expect(bar, STG_TX);
        tma2d(st, &tmX, 64 * kb, 128 * rt, bar);
        tma3d_mc(st + 16384 + rank * 16384, &tmW, 80 * cg, 64 * kb + 32 * rank, 0, bar);
        tma3d_mc(st + 16384 + rank * 16384 + 12288, &tmWt, 80 * cg + 64, 64 * kb + 32 * rank, 0, bar);
      }
      mbar_expect(sb + B_KX, 7680);
    }
    __syncwarp();
    STAMPW(64);
  } else {
    cl_arrive();
  }

  if (warp < 8) {
    const int wg = warp >> 2, w = warp & 3;
    {
      uint32_t wv[4];
#pragma unroll
      for (int i = 0; i < 4; i++) { int idx = tid + 256 * i; wv[i] = idx < 800 ? __ldg(prm.wphi + cg * 800 + idx) : 0u; }
#pragma unroll
      for (int i = 0; i < 4; i++) { int idx = tid + 256 * i; if (idx < 800) sts128(sb + OFF_PHI + idx * 16, 0, 0, 0, 0); }
      bar_sync(1, 256);
      if (tid == 0) STAMP(65);
#pragma unroll
      for (int i = 0; i < 4; i++) {
        int idx = tid + 256 * i;
        if (idx < 800) {
          int kk = idx / 10, j = idx - kk * 10, h = kk / 20;
          sts32(sb + OFF_PHI + j * 1280 + kk * 16 + h * 4, wv[i]);
        }
      }
      fence_async();
    }
    asm volatile("setmaxnreg.inc.sync.aligned.u32 176;");
    float acc[120];
#pragma unroll
    for (int i = 0; i < 120; i++) acc[i] = 0.f;
    reg_fence<120>(acc);
    cl_wait();
    STAMPW(0 + warp);
    const int pA = cg < 3 ? cg : 3, pB = cg < 3 ? 3 : 4;
#pragma unroll 1
    for (int kb = 0; kb < 10; kb++) {
      const int s = kb % 3;
      const uint32_t st = sb + OFF_S + ((3 - s) % 3) * STG;
      mbar_wait_nt(sb + B_FULL + 8 * s, (kb / 3) & 1);
      if (warp == 0) STAMPM(40 + kb);
      if (warp == 4) STAMPM(130 + kb);
      const uint64_t da = mkdesc(st + wg * 8192, 16, 1024, 1);
      const uint64_t db = mkdesc(st + 16384, 4096, 1024, 1);
      const uint64_t dt = mkdesc(st + 16384 + 12288, 1024, 256, 3);
      wg_fence();
#pragma unroll
      for (int ks = 0; ks < 2; ks++) {
        wgmma_ss<192, 0, 1>(acc, da + 2 * ks, db + ks * 128, 1);
        wgmma_ss<48, 0, 1>(acc + 96, da + 2 * ks, dt + ks * 32, 1);
      }
      wg_commit();
      wg_wait<1>();
      if (kb > 0 && lane < 2) mbar_arrive_cl(sb + B_EMPTY + 8 * ((kb + 2) % 3), lane);
      if (w == 0) STAMPM(159 + 10 * wg + kb);
      wg_fence();
#pragma unroll
      for (int ks = 0; ks < 2; ks++) {
        wgmma_ss<192, 0, 1>(acc, da + 4 + 2 * ks, db + 1024 + ks * 128, 1);
        wgmma_ss<48, 0, 1>(acc + 96, da + 4 + 2 * ks, dt + 1024 + ks * 32, 1);
      }
      wg_commit();
      if (w == 0) STAMPM(140 + 10 * wg + kb);
      if (kb == pA) {
        const int tt = (lane >> 1) & 3, row = 64 * ((warp >> 1) & 1) + 16 * tt + 4 * (lane >> 3) + 2 * wg + (lane & 1);
        const uint32_t ra = st + row * 128 + (((warp & 1) ^ (2 * tt) ^ (row & 7)) * 16);
        uint4 v0 = ldsm4t(ra), v1 = ldsm4t(ra ^ 32), v2 = ldsm4t(ra ^ 64), v3 = ldsm4t(ra ^ 96);
        if (t & 1) { uint4 u = v0; v0 = v1; v1 = u; u = v2; v2 = v3; v3 = u; }
        if (t & 2) { uint4 u = v0; v0 = v2; v2 = u; u = v1; v1 = v3; v3 = u; }
        unsigned char* dst = prm.s->xT + (64 * cg + 8 * (warp & 1) + g) * 4096 + wg * 2048 + (127 - 8 * rt - 4 * ((warp >> 1) & 1) - t) * 16;
        __stcg((uint4*)dst, v0); __stcg((uint4*)(dst + 65536), v1); __stcg((uint4*)(dst + 131072), v2); __stcg((uint4*)(dst + 196608), v3);
      } else if (kb == pB) {
        const int tt = (lane >> 1) & 3, row = 32 * (cg & 3) + 16 * (tt & 1) + 4 * (lane >> 3) + (tt & 2) + (lane & 1);
        const uint4 v = ldsm4t(st + row * 128 + ((warp ^ (row & 7)) * 16));
        __stcg((uint4*)(prm.s->xT + (512 + 64 * (cg >> 2) + 8 * warp + g) * 4096 + (t >> 1) * 2048 + (127 - 8 * rt - 2 * (cg & 3) - (t & 1)) * 16), v);
        bar_arrive(8, 288);
      }
    }
    wg_wait<0>();
    if (lane < 2) mbar_arrive_cl(sb + B_EMPTY, lane);
    if (w == 0) STAMPM(169 + 10 * wg);
    reg_fence<120>(acc);
    STAMPW(8 + warp);
    uint32_t ph0[20], ph1[20];
    float pq[40];
    {
      float pk[40];
      const uint64_t dphi = mkdesc(sb + OFF_PHI, 128, 1280, 0);
      const uint32_t rg = (8 * wg + 2 * w) * 128;
      mbar_wait(sb + B_EMPTY + 16, 0);
      {
        uint32_t va[20];
#pragma unroll
        for (int j = 0; j < 10; j++) {
          const int bv = j < 8 ? 16 + j : 20 + j;
          va[2 * j] = pack(acc[4 * bv], acc[4 * bv + 1]); va[2 * j + 1] = pack(acc[4 * bv + 2], acc[4 * bv + 3]);
        }
        const uint32_t v0 = sb + OFF_VB + rg + (lane & 15) * 16;
        const uint32_t hi = lane >> 4;
        stsm4(v0 + (0 + hi) * 2048, va[0], va[1], va[2], va[3]);
        stsm4(v0 + (3 + hi) * 2048, va[4], va[5], va[6], va[7]);
        stsm4(v0 + (5 + hi) * 2048, va[8], va[9], va[10], va[11]);
        stsm4(v0 + (7 + 2 * hi) * 2048, va[12], va[13], va[14], va[15]);
        stsm4(v0 + (10 + hi) * 2048, va[16], va[17], va[18], va[19]);
        sts128(v0 + (2 + 6 * hi) * 2048, 0x3F803F80u, 0x3F803F80u, 0x3F803F80u, 0x3F803F80u);
      }
      uint32_t fq[20];
#pragma unroll
      for (int j = 0; j < 10; j++) {
        const int bq = j < 8 ? j : 16 + j;
        fq[2 * j] = pack(acc[4 * bq], acc[4 * bq + 1]); fq[2 * j + 1] = pack(acc[4 * bq + 2], acc[4 * bq + 3]);
      }
      uint32_t fa[20];
#pragma unroll
      for (int j = 0; j < 10; j++) {
        const int bk = j < 8 ? 8 + j : 18 + j;
        fa[2 * j] = pack(acc[4 * bk], acc[4 * bk + 1]); fa[2 * j + 1] = pack(acc[4 * bk + 2], acc[4 * bk + 3]);
      }
      reg_fence<20>(fa); reg_fence<20>(fq);
      wg_fence();
#pragma unroll
      for (int s = 0; s < 5; s++) wgmma_rs<80, 1>(pk, fa[4 * s], fa[4 * s + 1], fa[4 * s + 2], fa[4 * s + 3], dphi + 16 * s, s > 0);
      wg_commit();
#pragma unroll
      for (int s = 0; s < 5; s++) wgmma_rs<80, 1>(pq, fq[4 * s], fq[4 * s + 1], fq[4 * s + 2], fq[4 * s + 3], dphi + 16 * s, s > 0);
      wg_commit();
      wg_wait<1>();
      reg_fence<40>(pk);
      if (warp == 0) STAMPW(66);
      softmax2(pk, ph0, ph1);
      mbar_wait(sb + B_EMPTY, 1);
      const uint32_t a0 = sb + OFF_PHIK + t * PHIK_HS + rg + g * 16;
#pragma unroll
      for (int c = 0; c < 5; c++) {
        sts128(a0 + c * 2048, ph0[4 * c], ph0[4 * c + 1], ph0[4 * c + 2], ph0[4 * c + 3]);
        sts128(a0 + c * 2048 + 128, ph1[4 * c], ph1[4 * c + 1], ph1[4 * c + 2], ph1[4 * c + 3]);
      }
    }
    fence_async();
    bar_sync(1, 256);
    STAMPW(16 + warp);
    const unsigned ep1 = (ld_rlx(cnt + C_DONE * 32) >> 7) + 1;
    {
      float kv[32];
      wg_fence();
#pragma unroll
      for (int hh = 0; hh < 2; hh++) {
        const uint64_t da = mkdesc(sb + OFF_PHIK + (2 * wg + hh) * PHIK_HS, 128, 2048, 0);
        const uint64_t db = mkdesc(sb + OFF_VB + (6 * wg + 2 * hh) * 2048, 128, 2048, 0);
#pragma unroll
        for (int s = 0; s < 8; s++) wgmma_ss<32, 1, 1>(kv + 16 * hh, da + 16 * s, db + 16 * s, s > 0);
      }
      wg_commit();
      mbar_wait(sb + B_Z, 0);
      wg_wait<0>();
      reg_fence<32>(kv);
      reg_fence<40>(pq);
      if (warp == 0) STAMPW(67);
      if (w < 3) {
        float v[2][12];
#pragma unroll
        for (int r = 0; r < 2; r++) {
          v[r][0] = kv[2 * r]; v[r][1] = kv[2 * r + 1]; v[r][2] = kv[4 + 2 * r]; v[r][3] = kv[5 + 2 * r];
          v[r][4] = t < 2 ? kv[12 + 2 * r] : kv[8 + 2 * r]; v[r][5] = t < 2 ? kv[13 + 2 * r] : 0.f;
          v[r][6] = kv[24 + 2 * r]; v[r][7] = kv[25 + 2 * r]; v[r][8] = kv[28 + 2 * r]; v[r][9] = kv[29 + 2 * r];
          v[r][10] = t < 2 ? kv[16 + 2 * r] : kv[20 + 2 * r]; v[r][11] = t < 2 ? 0.f : kv[21 + 2 * r];
        }
        const uint32_t xa = sb + OFF_KX + w * 3072 + lane * 16;
        if (wg != rank) {
          const uint32_t ra = mapa(xa, wg), rb = mapa(sb + B_KX, wg);
#pragma unroll
          for (int r = 0; r < 2; r++)
            if (r == 0 || w < 2)
#pragma unroll
              for (int i = 0; i < 3; i++) st_async4(ra + r * 1536 + i * 512, v[r][4 * i], v[r][4 * i + 1], v[r][4 * i + 2], v[r][4 * i + 3], rb);
        } else {
          float* b0 = prm.s->kv + (cg * 2 + rank) * 2560 + w * 1024 + lane * 4;
          mbar_wait(sb + B_KX, 0);
          float4 u[2][3];
#pragma unroll
          for (int r = 0; r < 2; r++)
            if (r == 0 || w < 2)
#pragma unroll
              for (int i = 0; i < 3; i++) u[r][i] = lds128f(xa + r * 1536 + i * 512);
#pragma unroll
          for (int r = 0; r < 2; r++)
            if (r == 0 || w < 2) {
              float* b = b0 + r * 512;
              red4(b, v[r][0] + u[r][0].x, v[r][1] + u[r][0].y, v[r][2] + u[r][0].z);
              red4(b + 128, v[r][3] + u[r][0].w, v[r][4] + u[r][1].x, v[r][5] + u[r][1].y);
              red4(b + 256, v[r][6] + u[r][1].z, v[r][7] + u[r][1].w, v[r][8] + u[r][2].x);
              red4(b + 384, v[r][9] + u[r][2].y, v[r][10] + u[r][2].z, v[r][11] + u[r][2].w);
            }
          bar_arrive(2, 128);
          if (w == 0) STAMPW(98);
        }
      }
      __syncwarp();
      if (lane < 4) mbar_arrive_cl(sb + B_EMPTYO + 8 * (lane >> 1), lane & 1);
    }
    softmax2(pq, ph0, ph1);
    reg_fence<20>(ph0); reg_fence<20>(ph1);
    STAMPW(24 + warp);
    {
      const int h = lane >> 3, fb = (lane >> 2) & 1;
      const float* src = prm.s->kv + (cg * 2 + (h >> 1)) * 2560 + (warp >> 2) * 512 + (h & 1) * 256 + ((2 * (warp & 3) + fb) * 4 + t) * 4;
      const int j0 = t + 2 * (h & 1), j2 = (h & 1) ? (t == 0 ? 10 : t - 2) : 8 + t;
      const bool has2 = t != ((h & 1) ? 1 : 3);
      const uint32_t dst = sb + OFF_KVB + warp * 128 + (2 * h + fb) * 16 + 4 * h;
      float4 f[3][2];
      if (lane == 0) poll(cnt + (C_KV + cg) * 32, 16 * ep1);
      __syncwarp();
      if (warp == 0) STAMPW(50);
#pragma unroll
      for (int i = 0; i < 3; i++)
        if (i < 2 || warp < 4) { f[i][0] = ld_rlx4(src + i * 1024); f[i][1] = ld_rlx4(src + i * 1024 + 128); }
#pragma unroll
      for (int i = 0; i < 3; i++)
        if (i < 2 || warp < 4) {
          sts32(dst + i * 1024 + j0 * KVB_S, pack(f[i][0].x, f[i][0].y));
          sts32(dst + i * 1024 + (j0 + 4) * KVB_S, pack(f[i][0].z, f[i][1].x));
          if (has2) sts32(dst + i * 1024 + j2 * KVB_S, pack(f[i][1].y, f[i][1].z));
        }
    }
    fence_async();
    bar_sync(1, 256);
    {
      float p[44];
      if (warp == 0) STAMPW(68);
      const uint64_t db = mkdesc(sb + OFF_KVB, 128, KVB_S, 0);
      wg_fence();
#pragma unroll
      for (int s = 0; s < 10; s++) wgmma_rs<88, 1>(p, ph0[2 * s], ph1[2 * s], ph0[2 * s + 1], ph1[2 * s + 1], db + 16 * s, s > 0);
      wg_commit();
      wg_wait<0>();
      reg_fence<44>(p);
      if (warp == 0) STAMPW(69);
      if (lane < 4) mbar_arrive_cl(sb + B_EMPTYO + 16 + 8 * (lane >> 1), lane & 1);
      const float r0 = rcp(p[40] + 1e-6f), r1 = rcp(p[42] + 1e-6f);
      uint32_t* o = (uint32_t*)(prm.s->o + (rt * 8 + cg) * 20480 + (8 * wg + 2 * w) * 128) + lane;
#pragma unroll
      for (int j = 0; j < 10; j++) {
        __stcg(o + j * 512, pack(p[4 * j] * r0, p[4 * j + 1] * r0));
        __stcg(o + j * 512 + 32, pack(p[4 * j + 2] * r1, p[4 * j + 3] * r1));
      }
      __syncwarp();
      if (lane == 0) red_rel(cnt + (C_O + rt) * 32 + cg);
    }
    if (warp == 0) STAMPW(51);
    float p[40];
#pragma unroll
    for (int i = 0; i < 40; i++) p[i] = 0.f;
    reg_fence<40>(p);
    mbar_wait(sb + B_WO, 0);
#pragma unroll 1
    for (int i = 0; i < 8; i++) {
      const int st = i & 3;
      const uint32_t oa = sb + (st < 2 ? OFF_S : OFF_PHI) + (st & 1) * 20480 + wg * 1024;
      const uint32_t wa = OFF_WO + (((i + 3) & 7) - 3) * 10240;
      const uint32_t ta = OFF_WOT + (i >> 2) * 10240 + (i & 3) * 32;
      const uint64_t da = mkdesc(oa, 2048, 128, 0);
      const uint64_t db = mkdesc(sb + wa, ta - wa, 1024, 1);
      mbar_wait(sb + B_FULLO + 8 * st, i >> 2);
      if (warp == 0) STAMPW(52 + i);
      wg_fence();
#pragma unroll
      for (int ks = 0; ks < 5; ks++) wgmma_ss<80, 0, 1>(p, da + 256 * ks, db + 128 * ks, 1);
      wg_commit();
      wg_wait<0>();
      if (i < 6 && lane < 2) mbar_arrive_cl(sb + B_EMPTYO + 8 * st, lane);
    }
    reg_fence<40>(p);
    if (warp == 0) STAMPW(60);
    mbar_wait(sb + B_Y, 0);
    mbar_wait(sb + B_EMPTYO + 8, 0);
    if (warp == 0) STAMPW(61);
    {
      const int r0 = 64 * wg + 16 * w + g;
      const float l0 = __uint_as_float(lds32(sb + OFF_G + r0 * 4)), l1 = __uint_as_float(lds32(sb + OFF_G + r0 * 4 + 32));
      const float g0 = rcp(1.f + ex2(-1.4426950408889634f * l0)), g1 = rcp(1.f + ex2(-1.4426950408889634f * l1));
      const uint32_t ya = sb + OFF_S + ((lane >> 4) * 8 + (lane & 7)) * 256 + (((8 * wg + 2 * w + ((lane >> 3) & 1)) ^ (lane & 7)) * 16);
      const uint32_t ob = sb + OFF_S + 20480 + warp * 2560;
      const uint32_t oa = ob + (lane & 15) * 160 + (lane >> 4) * 16;
#pragma unroll
      for (int j = 0; j < 5; j++) {
        const uint4 y = ldsm4t(ya + j * 4096);
        const float* a = p + 8 * j;
        uint32_t o0 = pack(fmaf(g0, a[0] - blo(y.x), blo(y.x)), fmaf(g0, a[1] - bhi(y.x), bhi(y.x)));
        uint32_t o1 = pack(fmaf(g1, a[2] - blo(y.y), blo(y.y)), fmaf(g1, a[3] - bhi(y.y), bhi(y.y)));
        uint32_t o2 = pack(fmaf(g0, a[4] - blo(y.z), blo(y.z)), fmaf(g0, a[5] - bhi(y.z), bhi(y.z)));
        uint32_t o3 = pack(fmaf(g1, a[6] - blo(y.w), blo(y.w)), fmaf(g1, a[7] - bhi(y.w), bhi(y.w)));
        stsm4(oa + j * 32, o0, o1, o2, o3);
      }
      fence_async();
      __syncwarp();
      if (lane == 0) {
        tma_st2d(&tmOut, ob, 80 * ct3, 128 * rt3 + 16 * warp);
        asm volatile("cp.async.bulk.commit_group;\ncp.async.bulk.wait_group.read 0;" ::: "memory");
      }
    }
    STAMPW(32 + warp);
  } else if (warp < 12) {
    asm volatile("setmaxnreg.dec.sync.aligned.u32 112;");
    const int w = warp & 3, th = tid & 127;
    {
      const int pi = cta * 640 + th;
      uint16_t n_lar = __ldg(prm.lar + pi), n_aim = __ldg(prm.aim + pi), n_cre = __ldg(prm.cre + pi), n_cim = __ldg(prm.cim + pi);
      uint16_t n_ldt = __ldg(prm.ldt + 5 * cta);
      uint16_t m_lar = __ldg(prm.lar + pi + 128), m_aim = __ldg(prm.aim + pi + 128), m_cre = __ldg(prm.cre + pi + 128), m_cim = __ldg(prm.cim + pi + 128);
      uint16_t m_ldt = __ldg(prm.ldt + 5 * cta + 1);
      KPrep k;
      kprep(k, n_lar, n_aim, n_cre, n_cim, n_ldt);
      cl_wait();
      if (w == 0) STAMPW(92);
      const uint32_t ea = sb + ((th & 63) >> 3) * 256 + (th & 7) * 16;
      const int gq = w >> 1;
#pragma unroll 1
      for (int j = 0; j < 5; j++) {
        {
          const uint32_t ba = ea + OFF_KB + gq * 6144;
          sts128(ba, k.B[0], k.B[1], k.B[2], k.B[3]); sts128(ba + 128, k.B[4], k.B[5], k.B[6], k.B[7]);
          sts128(ba + 2048, k.B[8], k.B[9], k.B[10], k.B[11]); sts128(ba + 2048 + 128, k.B[12], k.B[13], k.B[14], k.B[15]);
          sts128(ba + 4096, k.B[16], k.B[17], k.B[18], 0); sts128(ba + 4096 + 128, k.B[19], k.B[20], k.B[21], 0);
          const uint32_t aa = ea + OFF_KA + gq * 8192;
#pragma unroll
          for (int c = 0; c < 4; c++) {
            cf v[8];
            v[0] = k.S[c];
#pragma unroll
            for (int r = 1; r < 8; r++) v[r] = cmul(k.S[c], k.T[r]);
            sts128(aa + c * 2048, pack(v[0].x, v[1].x), pack(v[2].x, v[3].x), pack(v[4].x, v[5].x), pack(v[6].x, v[7].x));
            sts128(aa + c * 2048 + 128, pack(v[0].y, v[1].y), pack(v[2].y, v[3].y), pack(v[4].y, v[5].y), pack(v[6].y, v[7].y));
          }
        }
        if (w == 0 && j == 1) STAMPW(100);
        fence_async();
        if (w == 0 && j == 1) STAMPW(101);
        bar_sync(4, 128);
        if (w == 0 && j == 1) STAMPW(102);
        float kc[24];
        {
          const uint64_t da = mkdesc(sb + OFF_KA, 128, 2048, 0), db = mkdesc(sb + OFF_KB, 128, 2048, 0);
          wg_fence();
#pragma unroll
          for (int s = 0; s < KMMA; s++) wgmma_ss<48, 1, 1>(kc, da + 16 * s, db + 16 * s, s > 0);
          wg_commit();
        }
        kprep(k, m_lar, m_aim, m_cre, m_cim, m_ldt);
        if (j < 3) {
          const int q = pi + 128 * (j + 2);
          m_lar = __ldg(prm.lar + q); m_aim = __ldg(prm.aim + q); m_cre = __ldg(prm.cre + q); m_cim = __ldg(prm.cim + q);
          m_ldt = __ldg(prm.ldt + 5 * cta + j + 2);
        }
        reg_fence<22>(k.B);
        if (w == 0 && j == 1) STAMPW(103);
        wg_wait<0>();
        reg_fence<24>(kc);
        if (w == 0 && j == 1) STAMPW(104);
        bar_sync(6, 192);
        if (w == 0 && j == 1) STAMPW(105);
        if (j == 4) bar_arrive(7, 160);
        {
          const uint32_t ra = sb + OFF_KR + gq * 2592;
#pragma unroll
          for (int r = 0; r < 2; r++) {
            const int i = 16 * (w & 1) + g + 8 * r;
            float v[6];
#pragma unroll
            for (int c = 0; c < 3; c++) { v[2 * c] = gq ? kc[12 + 4 * c + 2 * r] : kc[4 * c + 2 * r]; v[2 * c + 1] = gq ? kc[13 + 4 * c + 2 * r] : kc[1 + 4 * c + 2 * r]; }
            sts64f(ra + (8 * i + 2 * t) * 4, v[0], v[1]);
            sts64f(ra + (t < 2 ? 256 + 4 * i + 2 * t : 256 + 64 * t + 2 * i) * 4, v[2], v[3]);
            if (t < 2 || (t == 2 && i == 0)) sts32(ra + (512 + 64 * t + i) * 4, __float_as_uint(v[4]));
            if (t < 2) sts32(ra + (544 + 64 * t + i) * 4, __float_as_uint(v[5]));
          }
        }
        bar_arrive(5, 192);
        if (w == 0) STAMPW(85 + j);
      }
    }
#pragma unroll 1
    for (int j = 0; j < 5; j++) {
      const uint32_t ka = sb + OFF_KT + (4 - j) * 4160 + 2 * (2064 - 16 * w - 2 * g + 4 * t);
      float acc[64];
      uint32_t a0[8], a1[8];
#pragma unroll
      for (int i = 0; i < 64; i++) acc[i] = 0.f;
      reg_fence<64>(acc);
      conv_load<0>(ka, a0);
      mbar_wait(sb + B_FULLU + 8 * (j & 1), (j >> 1) & 1);
      if (w == 0) STAMPW(70 + j);
      ConvLoop<0>::run(acc, ka, mkdesc(sb + OFF_U + (j & 1) * 4480, 2240, 128, 0), a0, a1);
      wg_wait<0>();
      reg_fence<64>(acc);
      if (w == 0) STAMPW(75 + j);
      bar_sync(6, 192);
      const uint32_t pa = sb + OFF_P + w * 4096 + ((lane >> 3) & 1) * 2048 + ((lane >> 4) * 8 + (lane & 7)) * 16;
#pragma unroll
      for (int i = 0; i < 8; i++) {
        const float* a = acc + 8 * i;
        stsm4t(pa + i * 256, pack(a[0], a[1]), pack(a[2], a[3]), pack(a[4], a[5]), pack(a[6], a[7]));
      }
      bar_arrive(5, 192);
    }
  } else {
    asm volatile("setmaxnreg.dec.sync.aligned.u32 48;");
    if (warp == 12) {
      cl_wait();
      if (lane == 0) {
        asm volatile("prefetch.tensormap [%0];" ::"l"(&tmWo) : "memory");
        asm volatile("prefetch.tensormap [%0];" ::"l"(&tmOut) : "memory");
        const int kv_ = 8 + (cg >> 2), p0 = cg < 3 ? 4 : 5;
#pragma unroll 1
        for (int p = 0; p < 7; p++) {
          const int s = p % 3;
          const uint32_t st = sb + OFF_S + ((3 - s) % 3) * STG, bar = sb + B_FULL + 8 * s;
          int kb = p + 6 - p0;
          if (cg >= 3 && kb >= cg) kb++;
          if (kb >= kv_) kb++;
          if (p + 4 == p0) kb = kv_;
          if (p + 5 == p0) kb = cg;
          mbar_wait(sb + B_EMPTY + 8 * s, (p / 3) & 1);
          STAMP(180 + p);
          mbar_expect(bar, STG_TX);
          tma2d(st, &tmX, 64 * kb, 128 * rt, bar);
          tma3d_mc(st + 16384 + rank * 16384, &tmW, 80 * cg, 64 * kb + 32 * rank, 0, bar);
          tma3d_mc(st + 16384 + rank * 16384 + 12288, &tmWt, 80 * cg + 64, 64 * kb + 32 * rank, 0, bar);
          STAMP(190 + p);
        }
        const uint32_t wb = sb + B_WO;
        mbar_wait(sb + B_EMPTY + 8, 0);
        mbar_arrive(sb + B_T);
        mbar_expect(wb, 20480);
        for (int u = 3; u < 5; u++) tma5d(sb + OFF_WO + u * 10240, &tmWo, 80 * ct3, 0, 0, 0, u, wb);
        mbar_wait(sb + B_EMPTY + 16, 0);
        mbar_expect(wb, 30720);
        for (int u = 0; u < 3; u++) tma5d(sb + OFF_WO + u * 10240, &tmWo, 80 * ct3, 0, 0, 0, u, wb);
      }
      __syncwarp();
      const unsigned ep1 = (ld_rlx(cnt + C_DONE * 32) >> 7) + 1;
      bar_sync(2, 128);
      STAMPW(90);
      if (lane == 0) red_rel(cnt + (C_KV + cg) * 32);
      STAMPW(91);
      if (lane == 0) {
        const uint32_t wb = sb + B_WO;
        mbar_wait(sb + B_EMPTYO, 0);
        mbar_expect(wb, 30720);
        for (int u = 5; u < 8; u++) tma5d(sb + OFF_WO + (u - 8) * 10240, &tmWo, 80 * ct3, 0, 0, 0, u, wb);
      }
      __syncwarp();
      {
        unsigned ready = 0;
        int next = 0, n = 0;
        while (next < 8) {
          bool ok = false;
          if (lane < 8 && !((ready >> lane) & 1)) ok = (int)(ld_acq(cnt + (C_O + rt3) * 32 + lane) - 8 * ep1) >= 0;
          ready |= __ballot_sync(0xffffffffu, ok);
          while (next < 8 && ((ready >> next) & 1)) {
            if (lane == next) {
              const int st = next & 3;
              const uint32_t oa = sb + (st < 2 ? OFF_S : OFF_PHI) + (st & 1) * 20480;
              mbar_wait(sb + B_EMPTYO + 8 * st, next >> 2);
              fence_async_g();
              mbar_expect(sb + B_FULLO + 8 * st, 20480);
              bulk_ld_mc(oa + rank * 10240, prm.s->o + (rt3 * 8 + next) * 20480 + rank * 10240, 10240, sb + B_FULLO + 8 * st);
            }
            __syncwarp();
            next++;
          }
          if (++n > SPIN_MAX) __trap();
        }
      }
      if (lane == 0) {
        poll(cnt + (C_G + rt3) * 32, 8 * ep1);
        poll(cnt + (C_Y + ct3) * 32, 32 * ep1);
        mbar_wait(sb + B_EMPTYO, 0);
        fence_async_g();
        mbar_expect(sb + B_Y, 20480 + 512);
        bulk_ld(sb + OFF_S, prm.s->y + (rt3 * 640 + 80 * ct3) * 256, 20480, sb + B_Y);
        bulk_ld(sb + OFF_G, prm.s->gate + rt3 * 128, 512, sb + B_Y);
        red_rlx(cnt + C_DONE * 32);
      }
    } else if (warp == 13) {
      const unsigned ep1 = (ld_rlx(cnt + C_DONE * 32) >> 7) + 1;
      {
        float4* z = (float4*)prm.s->kv + cg * 1280 + rt * 80;
        z[lane] = make_float4(0.f, 0.f, 0.f, 0.f); z[lane + 32] = make_float4(0.f, 0.f, 0.f, 0.f);
        if (lane < 16) z[lane + 64] = make_float4(0.f, 0.f, 0.f, 0.f);
      }
#pragma unroll
      for (int i = 0; i < 2; i++)
        if ((lane & 15) < 12) sts128(sb + OFF_U + (2 * i + (lane >> 4)) * 2240 + 2048 + (lane & 15) * 16, 0, 0, 0, 0);
      fence_async();
      bar_sync(8, 288);
      STAMPW(93);
      if (lane == 0) {
        red_rel(cnt + C_X * 32);
        STAMP(94);
        poll(cnt + C_X * 32, 128 * ep1);
        fence_async_g();
        for (int j = 0; j < 2; j++) {
          const uint32_t bar = sb + B_FULLU + 8 * j, ub = sb + OFF_U + j * 4480;
          const unsigned char* src = prm.s->xT + (5 * cta + j) * 4096;
          mbar_expect(bar, 4096);
          bulk_ld(ub, src, 2048, bar);
          bulk_ld(ub + 2240, src + 2048, 2048, bar);
        }
      }
      __syncwarp();
      STAMPW(95);
      bar_sync(7, 160);
#pragma unroll 8
      for (int i = 0; i < 56; i++) sts128(sb + OFF_KVB + (i * 32 + lane) * 16, 0, 0, 0, 0);
      fence_async();
      __syncwarp();
      if (lane == 0) mbar_arrive(sb + B_Z);
      STAMPW(96);
      mbar_wait(sb + B_T, 0);
      {
        const int c = lane & 1, rr = lane >> 1;
        const uint16_t* src = prm.wo + (20 * ((rr >> 1) & 3) + 2 * (rr >> 3) + (rr & 1)) * 640 + 80 * ct3 + 64 + 8 * c;
#pragma unroll
        for (int q = 0; q < 4; q++) {
          const uint32_t d = sb + OFF_WOT + rr * 128 + (((2 * q + c) ^ (rr & 7)) * 16);
#pragma unroll
          for (int i = 0; i < 10; i++)
            asm volatile("cp.async.cg.shared.global [%0], [%1], 16;" ::"r"(d + (i / 5) * 10240 + (i % 5) * 2048), "l"(src + (80 * (q + 4 * (i / 5)) + 4 * (i % 5)) * 640) : "memory");
        }
      }
      asm volatile("cp.async.wait_all;" ::: "memory");
      fence_async();
      __syncwarp();
      if (lane == 0) mbar_arrive(sb + B_WO);
      STAMPW(97);
      {
        const uint4* xr = prm.x + (128 * rt + 16 * cg + (lane >> 4)) * 80 + (lane & 15);
        const uint4* gw = prm.gw + (lane & 15);
#pragma unroll 1
        for (int h = 0; h < 2; h++) {
          float a[4] = {0.f, 0.f, 0.f, 0.f};
#pragma unroll 1
          for (int j = 0; j < 5; j++) {
            uint4 xv[4];
            const uint4 w4 = __ldg(gw + j * 16);
#pragma unroll
            for (int i = 0; i < 4; i++) xv[i] = __ldcg(xr + (4 * h + i) * 160 + j * 16);
#pragma unroll
            for (int i = 0; i < 4; i++) {
              a[i] = fmaf(blo(xv[i].x), blo(w4.x), a[i]); a[i] = fmaf(bhi(xv[i].x), bhi(w4.x), a[i]);
              a[i] = fmaf(blo(xv[i].y), blo(w4.y), a[i]); a[i] = fmaf(bhi(xv[i].y), bhi(w4.y), a[i]);
              a[i] = fmaf(blo(xv[i].z), blo(w4.z), a[i]); a[i] = fmaf(bhi(xv[i].z), bhi(w4.z), a[i]);
              a[i] = fmaf(blo(xv[i].w), blo(w4.w), a[i]); a[i] = fmaf(bhi(xv[i].w), bhi(w4.w), a[i]);
            }
          }
#pragma unroll
          for (int i = 0; i < 4; i++) {
            a[i] += __shfl_xor_sync(0xffffffffu, a[i], 1); a[i] += __shfl_xor_sync(0xffffffffu, a[i], 2);
            a[i] += __shfl_xor_sync(0xffffffffu, a[i], 4); a[i] += __shfl_xor_sync(0xffffffffu, a[i], 8);
            if ((lane & 15) == 0) __stcg(prm.s->gate + 128 * rt + 16 * cg + 8 * h + 2 * i + (lane >> 4), a[i]);
          }
        }
        __syncwarp();
        if (lane == 0) red_rel(cnt + (C_G + rt) * 32);
        STAMPW(99);
      }
    } else {
      const int t64 = tid & 63;
      bar_arrive(6, 192);
      cl_wait();
#pragma unroll 1
      for (int j = 0; j < 5; j++) {
        const float dskip = bf2f(__ldg(prm.dsk + 5 * cta + j));
        bar_sync(5, 192);
#pragma unroll
        for (int i = 0; i < 3; i++) {
          const int idx = t64 + 64 * i;
          if (idx < 161) {
            const float4 a = lds128f(sb + OFF_KR + idx * 16), b = lds128f(sb + OFF_KR + 2592 + idx * 16);
            sts64(sb + OFF_KV16 + idx * 8, pack(a.x + b.x + (idx == 0 ? dskip : 0.f), a.y + b.y), pack(a.z + b.z, a.w + b.w));
          }
        }
        if (warp == 14 && j == 0) STAMPW(106);
        bar_sync(3, 64);
        if (warp == 14 && j == 0) STAMPW(107);
        const uint32_t kt = sb + OFF_KT + (4 - j) * 4160, kv = sb + OFF_KV16;
        const uint32_t dst = kt + 2 * (2064 - 16 * t64 - 16);
        expand16<3>(kv, 512 + 2 * t64, dst - 2048);
        if (t64 >= 32) expand16<2>(kv, 384 + 4 * (t64 - 32), dst);
        else if (t64 >= 16) expand16<1>(kv, 256 + 8 * (t64 - 16), dst);
        else expand16<0>(kv, 16 * t64, dst);
        if (t64 == 63) {
          sts128(kt + 2 * 2064, lds16(kv), 0, 0, 0);
          sts128(kt + 2 * 2064 + 16, 0, 0, 0, 0);
        }
        bar_arrive(6, 192);
        if (warp == 14 && j == 0) STAMPW(108);
      }
#pragma unroll 1
      for (int j = 0; j < 5; j++) {
        const int ch = 5 * cta + j;
        bar_sync(5, 192);
        if (j < 3 && t64 == 0) {
          const uint32_t bar = sb + B_FULLU + 8 * (j & 1), ub = sb + OFF_U + (j & 1) * 4480;
          const unsigned char* src = prm.s->xT + (ch + 2) * 4096;
          fence_async_g();
          mbar_expect(bar, 4096);
          bulk_ld(ub, src, 2048, bar);
          bulk_ld(ub + 2240, src + 2048, 2048, bar);
        }
#pragma unroll 1
        for (int it = 0; it < 2; it++) {
          const int th = t64 + 64 * it;
          uint4 e[4], o[4];
#pragma unroll
          for (int ww = 0; ww < 4; ww++) {
            const uint32_t pa = sb + OFF_P + ww * 4096 + (127 - th + ww) * 16, za = sb + OFF_U + 2048;
            e[ww] = lds128(th >= ww ? pa : za); o[ww] = lds128(th >= ww ? pa + 2048 : za);
          }
#define SUM4(f, a, c) ((f(a[0].c) + f(a[1].c)) + (f(a[2].c) + f(a[3].c)))
          unsigned char* yb = prm.s->y + ((th >> 3) * 640 + ch) * 256;
          const int c0 = 2 * (th & 7), sw = ch & 7;
          __stcg((uint4*)(yb + ((c0 ^ sw) * 16)), make_uint4(pack(SUM4(blo, e, x), SUM4(blo, o, x)), pack(SUM4(bhi, e, x), SUM4(bhi, o, x)),
                                                             pack(SUM4(blo, e, y), SUM4(blo, o, y)), pack(SUM4(bhi, e, y), SUM4(bhi, o, y))));
          __stcg((uint4*)(yb + (((c0 + 1) ^ sw) * 16)), make_uint4(pack(SUM4(blo, e, z), SUM4(blo, o, z)), pack(SUM4(bhi, e, z), SUM4(bhi, o, z)),
                                                                   pack(SUM4(blo, e, w), SUM4(blo, o, w)), pack(SUM4(bhi, e, w), SUM4(bhi, o, w))));
        }
        if (j < 4) bar_arrive(6, 192);
        if (warp == 14) STAMPW(80 + j);
      }
      __syncwarp();
      if (lane == 0) red_rel(cnt + (C_Y + (cta >> 4)) * 32 );
    }
  }
}

typedef CUresult (*EncFn)(CUtensorMap*, CUtensorMapDataType, cuuint32_t, void*, const cuuint64_t*, const cuuint64_t*, const cuuint32_t*,
                          const cuuint32_t*, CUtensorMapInterleave, CUtensorMapSwizzle, CUtensorMapL2promotion, CUtensorMapFloatOOBfill);
int enc(EncFn fn, CUtensorMap* m, void* p, int rank, const cuuint64_t* gd, const cuuint64_t* gs, const cuuint32_t* bd, CUtensorMapSwizzle sw) {
  const cuuint32_t es[5] = {1, 1, 1, 1, 1};
  return (int)fn(m, CU_TENSOR_MAP_DATA_TYPE_BFLOAT16, rank, p, gd, gs, bd, es, CU_TENSOR_MAP_INTERLEAVE_NONE, sw,
                 CU_TENSOR_MAP_L2_PROMOTION_L2_128B, CU_TENSOR_MAP_FLOAT_OOB_FILL_NONE);
}
int g_enc_err = 0;
}

extern "C" void kernel_launch(void* const* d_in, const int* in_sizes, int n_in, void* d_out, int out_size) {
  static EncFn fn = nullptr;
  static Scratch* scr = nullptr;
  if (!fn) {
    void* p = nullptr;
    cudaDriverEntryPointQueryResult qr;
    cudaGetDriverEntryPoint("cuTensorMapEncodeTiled", &p, cudaEnableDefault, &qr);
    fn = (EncFn)p;
    cudaGetSymbolAddress((void**)&scr, g_s);
    cudaFuncSetAttribute(fused_kernel, cudaFuncAttributeMaxDynamicSharedMemorySize, SMEM_BYTES);
  }
  CUtensorMap mX, mW, mWt, mWo, mOut;
  int e = 0;
  { cuuint64_t gd[2] = {640, 2048}, gs[1] = {1280}; cuuint32_t bd[2] = {64, 128}; e |= enc(fn, &mX, d_in[0], 2, gd, gs, bd, CU_TENSOR_MAP_SWIZZLE_128B); }
  { cuuint64_t gd[3] = {640, 640, 3}, gs[2] = {3840, 1280}; cuuint32_t bd[3] = {64, 32, 3}; e |= enc(fn, &mW, d_in[1], 3, gd, gs, bd, CU_TENSOR_MAP_SWIZZLE_128B) << 4; }
  { cuuint64_t gd[3] = {640, 640, 3}, gs[2] = {3840, 1280}; cuuint32_t bd[3] = {16, 32, 3}; e |= enc(fn, &mWt, d_in[1], 3, gd, gs, bd, CU_TENSOR_MAP_SWIZZLE_32B) << 8; }
  { cuuint64_t gd[5] = {640, 2, 4, 10, 8}, gs[4] = {1280, 25600, 2560, 102400}; cuuint32_t bd[5] = {64, 2, 4, 10, 1}; e |= enc(fn, &mWo, d_in[3], 5, gd, gs, bd, CU_TENSOR_MAP_SWIZZLE_128B) << 12; }
  { cuuint64_t gd[2] = {640, 2048}, gs[1] = {1280}; cuuint32_t bd[2] = {80, 16}; e |= enc(fn, &mOut, d_out, 2, gd, gs, bd, CU_TENSOR_MAP_SWIZZLE_NONE) << 20; }
  g_enc_err = e;
  if (e) return;
  Params prm;
  prm.s = scr; prm.wo = (const uint16_t*)d_in[3]; prm.lar = (const uint16_t*)d_in[5]; prm.aim = (const uint16_t*)d_in[6];
  prm.cre = (const uint16_t*)d_in[7]; prm.cim = (const uint16_t*)d_in[8]; prm.ldt = (const uint16_t*)d_in[9]; prm.dsk = (const uint16_t*)d_in[10];
  prm.wphi = (const uint32_t*)d_in[2]; prm.gw = (const uint4*)d_in[11]; prm.x = (const uint4*)d_in[0];
  fused_kernel<<<128, 512, SMEM_BYTES, cudaStreamPerThread>>>(prm, mX, mW, mWt, mWo, mOut);
}
```

```cpp
#include <cuda_runtime.h>
#include <cuda_bf16.h>
#include <cuda.h>
#include <stdint.h>

template<int N, int TA, int TB> __device__ __forceinline__ void wgmma_ss(float* d, uint64_t da, uint64_t db, int sd);
template<int N, int TB> __device__ __forceinline__ void wgmma_rs(float* d, uint32_t a0, uint32_t a1, uint32_t a2, uint32_t a3, uint64_t db, int sd);
template<> __device__ __forceinline__ void wgmma_ss<192,0,1>(float* d, uint64_t da, uint64_t db, int sd) {
  asm volatile("{\n.reg .pred p;\nsetp.ne.b32 p, %98, 0;\n"
  "wgmma.mma_async.sync.aligned.m64n192k16.f32.bf16.bf16 {%0,%1,%2,%3,%4,%5,%6,%7,%8,%9,%10,%11,%12,%13,%14,%15,%16,%17,%18,%19,%20,%21,%22,%23,%24,%25,%26,%27,%28,%29,%30,%31,%32,%33,%34,%35,%36,%37,%38,%39,%40,%41,%42,%43,%44,%45,%46,%47,%48,%49,%50,%51,%52,%53,%54,%55,%56,%57,%58,%59,%60,%61,%62,%63,%64,%65,%66,%67,%68,%69,%70,%71,%72,%73,%74,%75,%76,%77,%78,%79,%80,%81,%82,%83,%84,%85,%86,%87,%88,%89,%90,%91,%92,%93,%94,%95}, %96, %97, p, 1, 1, 0, 1;\n}\n"
  : "+f"(d[0]),"+f"(d[1]),"+f"(d[2]),"+f"(d[3]),"+f"(d[4]),"+f"(d[5]),"+f"(d[6]),"+f"(d[7]),"+f"(d[8]),"+f"(d[9]),"+f"(d[10]),"+f"(d[11]),"+f"(d[12]),"+f"(d[13]),"+f"(d[14]),"+f"(d[15]),"+f"(d[16]),"+f"(d[17]),"+f"(d[18]),"+f"(d[19]),"+f"(d[20]),"+f"(d[21]),"+f"(d[22]),"+f"(d[23]),"+f"(d[24]),"+f"(d[25]),"+f"(d[26]),"+f"(d[27]),"+f"(d[28]),"+f"(d[29]),"+f"(d[30]),"+f"(d[31]),"+f"(d[32]),"+f"(d[33]),"+f"(d[34]),"+f"(d[35]),"+f"(d[36]),"+f"(d[37]),"+f"(d[38]),"+f"(d[39]),"+f"(d[40]),"+f"(d[41]),"+f"(d[42]),"+f"(d[43]),"+f"(d[44]),"+f"(d[45]),"+f"(d[46]),"+f"(d[47]),"+f"(d[48]),"+f"(d[49]),"+f"(d[50]),"+f"(d[51]),"+f"(d[52]),"+f"(d[53]),"+f"(d[54]),"+f"(d[55]),"+f"(d[56]),"+f"(d[57]),"+f"(d[58]),"+f"(d[59]),"+f"(d[60]),"+f"(d[61]),"+f"(d[62]),"+f"(d[63]),"+f"(d[64]),"+f"(d[65]),"+f"(d[66]),"+f"(d[67]),"+f"(d[68]),"+f"(d[69]),"+f"(d[70]),"+f"(d[71]),"+f"(d[72]),"+f"(d[73]),"+f"(d[74]),"+f"(d[75]),"+f"(d[76]),"+f"(d[77]),"+f"(d[78]),"+f"(d[79]),"+f"(d[80]),"+f"(d[81]),"+f"(d[82]),"+f"(d[83]),"+f"(d[84]),"+f"(d[85]),"+f"(d[86]),"+f"(d[87]),"+f"(d[88]),"+f"(d[89]),"+f"(d[90]),"+f"(d[91]),"+f"(d[92]),"+f"(d[93]),"+f"(d[94]),"+f"(d[95]) : "l"(da), "l"(db), "r"(sd));
}
template<> __device__ __forceinline__ void wgmma_ss<48,0,1>(float* d, uint64_t da, uint64_t db, int sd) {
  asm volatile("{\n.reg .pred p;\nsetp.ne.b32 p, %26, 0;\n"
  "wgmma.mma_async.sync.aligned.m64n48k16.f32.bf16.bf16 {%0,%1,%2,%3,%4,%5,%6,%7,%8,%9,%10,%11,%12,%13,%14,%15,%16,%17,%18,%19,%20,%21,%22,%23}, %24, %25, p, 1, 1, 0, 1;\n}\n"
  : "+f"(d[0]),"+f"(d[1]),"+f"(d[2]),"+f"(d[3]),"+f"(d[4]),"+f"(d[5]),"+f"(d[6]),"+f"(d[7]),"+f"(d[8]),"+f"(d[9]),"+f"(d[10]),"+f"(d[11]),"+f"(d[12]),"+f"(d[13]),"+f"(d[14]),"+f"(d[15]),"+f"(d[16]),"+f"(d[17]),"+f"(d[18]),"+f"(d[19]),"+f"(d[20]),"+f"(d[21]),"+f"(d[22]),"+f"(d[23]) : "l"(da), "l"(db), "r"(sd));
}
template<> __device__ __forceinline__ void wgmma_ss<48,1,1>(float* d, uint64_t da, uint64_t db, int sd) {
  asm volatile("{\n.reg .pred p;\nsetp.ne.b32 p, %26, 0;\n"
  "wgmma.mma_async.sync.aligned.m64n48k16.f32.bf16.bf16 {%0,%1,%2,%3,%4,%5,%6,%7,%8,%9,%10,%11,%12,%13,%14,%15,%16,%17,%18,%19,%20,%21,%22,%23}, %24, %25, p, 1, 1, 1, 1;\n}\n"
  : "+f"(d[0]),"+f"(d[1]),"+f"(d[2]),"+f"(d[3]),"+f"(d[4]),"+f"(d[5]),"+f"(d[6]),"+f"(d[7]),"+f"(d[8]),"+f"(d[9]),"+f"(d[10]),"+f"(d[11]),"+f"(d[12]),"+f"(d[13]),"+f"(d[14]),"+f"(d[15]),"+f"(d[16]),"+f"(d[17]),"+f"(d[18]),"+f"(d[19]),"+f"(d[20]),"+f"(d[21]),"+f"(d[22]),"+f"(d[23]) : "l"(da), "l"(db), "r"(sd));
}
template<> __device__ __forceinline__ void wgmma_rs<80,1>(float* d, uint32_t a0, uint32_t a1, uint32_t a2, uint32_t a3, uint64_t db, int sd) {
  asm volatile("{\n.reg .pred p;\nsetp.ne.b32 p, %45, 0;\n"
  "wgmma.mma_async.sync.aligned.m64n80k16.f32.bf16.bf16 {%0,%1,%2,%3,%4,%5,%6,%7,%8,%9,%10,%11,%12,%13,%14,%15,%16,%17,%18,%19,%20,%21,%22,%23,%24,%25,%26,%27,%28,%29,%30,%31,%32,%33,%34,%35,%36,%37,%38,%39}, {%40,%41,%42,%43}, %44, p, 1, 1, 1;\n}\n"
  : "+f"(d[0]),"+f"(d[1]),"+f"(d[2]),"+f"(d[3]),"+f"(d[4]),"+f"(d[5]),"+f"(d[6]),"+f"(d[7]),"+f"(d[8]),"+f"(d[9]),"+f"(d[10]),"+f"(d[11]),"+f"(d[12]),"+f"(d[13]),"+f"(d[14]),"+f"(d[15]),"+f"(d[16]),"+f"(d[17]),"+f"(d[18]),"+f"(d[19]),"+f"(d[20]),"+f"(d[21]),"+f"(d[22]),"+f"(d[23]),"+f"(d[24]),"+f"(d[25]),"+f"(d[26]),"+f"(d[27]),"+f"(d[28]),"+f"(d[29]),"+f"(d[30]),"+f"(d[31]),"+f"(d[32]),"+f"(d[33]),"+f"(d[34]),"+f"(d[35]),"+f"(d[36]),"+f"(d[37]),"+f"(d[38]),"+f"(d[39]) : "r"(a0), "r"(a1), "r"(a2), "r"(a3), "l"(db), "r"(sd));
}
template<> __device__ __forceinline__ void wgmma_ss<32,1,1>(float* d, uint64_t da, uint64_t db, int sd) {
  asm volatile("{\n.reg .pred p;\nsetp.ne.b32 p, %18, 0;\n"
  "wgmma.mma_async.sync.aligned.m64n32k16.f32.bf16.bf16 {%0,%1,%2,%3,%4,%5,%6,%7,%8,%9,%10,%11,%12,%13,%14,%15}, %16, %17, p, 1, 1, 1, 1;\n}\n"
  : "+f"(d[0]),"+f"(d[1]),"+f"(d[2]),"+f"(d[3]),"+f"(d[4]),"+f"(d[5]),"+f"(d[6]),"+f"(d[7]),"+f"(d[8]),"+f"(d[9]),"+f"(d[10]),"+f"(d[11]),"+f"(d[12]),"+f"(d[13]),"+f"(d[14]),"+f"(d[15]) : "l"(da), "l"(db), "r"(sd));
}
template<> __device__ __forceinline__ void wgmma_rs<88,1>(float* d, uint32_t a0, uint32_t a1, uint32_t a2, uint32_t a3, uint64_t db, int sd) {
  asm volatile("{\n.reg .pred p;\nsetp.ne.b32 p, %49, 0;\n"
  "wgmma.mma_async.sync.aligned.m64n88k16.f32.bf16.bf16 {%0,%1,%2,%3,%4,%5,%6,%7,%8,%9,%10,%11,%12,%13,%14,%15,%16,%17,%18,%19,%20,%21,%22,%23,%24,%25,%26,%27,%28,%29,%30,%31,%32,%33,%34,%35,%36,%37,%38,%39,%40,%41,%42,%43}, {%44,%45,%46,%47}, %48, p, 1, 1, 1;\n}\n"
  : "+f"(d[0]),"+f"(d[1]),"+f"(d[2]),"+f"(d[3]),"+f"(d[4]),"+f"(d[5]),"+f"(d[6]),"+f"(d[7]),"+f"(d[8]),"+f"(d[9]),"+f"(d[10]),"+f"(d[11]),"+f"(d[12]),"+f"(d[13]),"+f"(d[14]),"+f"(d[15]),"+f"(d[16]),"+f"(d[17]),"+f"(d[18]),"+f"(d[19]),"+f"(d[20]),"+f"(d[21]),"+f"(d[22]),"+f"(d[23]),"+f"(d[24]),"+f"(d[25]),"+f"(d[26]),"+f"(d[27]),"+f"(d[28]),"+f"(d[29]),"+f"(d[30]),"+f"(d[31]),"+f"(d[32]),"+f"(d[33]),"+f"(d[34]),"+f"(d[35]),"+f"(d[36]),"+f"(d[37]),"+f"(d[38]),"+f"(d[39]),"+f"(d[40]),"+f"(d[41]),"+f"(d[42]),"+f"(d[43]) : "r"(a0), "r"(a1), "r"(a2), "r"(a3), "l"(db), "r"(sd));
}
template<> __device__ __forceinline__ void wgmma_ss<80,0,1>(float* d, uint64_t da, uint64_t db, int sd) {
  asm volatile("{\n.reg .pred p;\nsetp.ne.b32 p, %42, 0;\n"
  "wgmma.mma_async.sync.aligned.m64n80k16.f32.bf16.bf16 {%0,%1,%2,%3,%4,%5,%6,%7,%8,%9,%10,%11,%12,%13,%14,%15,%16,%17,%18,%19,%20,%21,%22,%23,%24,%25,%26,%27,%28,%29,%30,%31,%32,%33,%34,%35,%36,%37,%38,%39}, %40, %41, p, 1, 1, 0, 1;\n}\n"
  : "+f"(d[0]),"+f"(d[1]),"+f"(d[2]),"+f"(d[3]),"+f"(d[4]),"+f"(d[5]),"+f"(d[6]),"+f"(d[7]),"+f"(d[8]),"+f"(d[9]),"+f"(d[10]),"+f"(d[11]),"+f"(d[12]),"+f"(d[13]),"+f"(d[14]),"+f"(d[15]),"+f"(d[16]),"+f"(d[17]),"+f"(d[18]),"+f"(d[19]),"+f"(d[20]),"+f"(d[21]),"+f"(d[22]),"+f"(d[23]),"+f"(d[24]),"+f"(d[25]),"+f"(d[26]),"+f"(d[27]),"+f"(d[28]),"+f"(d[29]),"+f"(d[30]),"+f"(d[31]),"+f"(d[32]),"+f"(d[33]),"+f"(d[34]),"+f"(d[35]),"+f"(d[36]),"+f"(d[37]),"+f"(d[38]),"+f"(d[39]) : "l"(da), "l"(db), "r"(sd));
}
template<> __device__ __forceinline__ void wgmma_rs<16,0>(float* d, uint32_t a0, uint32_t a1, uint32_t a2, uint32_t a3, uint64_t db, int sd) {
  asm volatile("{\n.reg .pred p;\nsetp.ne.b32 p, %13, 0;\n"
  "wgmma.mma_async.sync.aligned.m64n16k16.f32.bf16.bf16 {%0,%1,%2,%3,%4,%5,%6,%7}, {%8,%9,%10,%11}, %12, p, 1, 1, 0;\n}\n"
  : "+f"(d[0]),"+f"(d[1]),"+f"(d[2]),"+f"(d[3]),"+f"(d[4]),"+f"(d[5]),"+f"(d[6]),"+f"(d[7]) : "r"(a0), "r"(a1), "r"(a2), "r"(a3), "l"(db), "r"(sd));
}
template<> __device__ __forceinline__ void wgmma_rs<32,0>(float* d, uint32_t a0, uint32_t a1, uint32_t a2, uint32_t a3, uint64_t db, int sd) {
  asm volatile("{\n.reg .pred p;\nsetp.ne.b32 p, %21, 0;\n"
  "wgmma.mma_async.sync.aligned.m64n32k16.f32.bf16.bf16 {%0,%1,%2,%3,%4,%5,%6,%7,%8,%9,%10,%11,%12,%13,%14,%15}, {%16,%17,%18,%19}, %20, p, 1, 1, 0;\n}\n"
  : "+f"(d[0]),"+f"(d[1]),"+f"(d[2]),"+f"(d[3]),"+f"(d[4]),"+f"(d[5]),"+f"(d[6]),"+f"(d[7]),"+f"(d[8]),"+f"(d[9]),"+f"(d[10]),"+f"(d[11]),"+f"(d[12]),"+f"(d[13]),"+f"(d[14]),"+f"(d[15]) : "r"(a0), "r"(a1), "r"(a2), "r"(a3), "l"(db), "r"(sd));
}
template<> __device__ __forceinline__ void wgmma_rs<48,0>(float* d, uint32_t a0, uint32_t a1, uint32_t a2, uint32_t a3, uint64_t db, int sd) {
  asm volatile("{\n.reg .pred p;\nsetp.ne.b32 p, %29, 0;\n"
  "wgmma.mma_async.sync.aligned.m64n48k16.f32.bf16.bf16 {%0,%1,%2,%3,%4,%5,%6,%7,%8,%9,%10,%11,%12,%13,%14,%15,%16,%17,%18,%19,%20,%21,%22,%23}, {%24,%25,%26,%27}, %28, p, 1, 1, 0;\n}\n"
  : "+f"(d[0]),"+f"(d[1]),"+f"(d[2]),"+f"(d[3]),"+f"(d[4]),"+f"(d[5]),"+f"(d[6]),"+f"(d[7]),"+f"(d[8]),"+f"(d[9]),"+f"(d[10]),"+f"(d[11]),"+f"(d[12]),"+f"(d[13]),"+f"(d[14]),"+f"(d[15]),"+f"(d[16]),"+f"(d[17]),"+f"(d[18]),"+f"(d[19]),"+f"(d[20]),"+f"(d[21]),"+f"(d[22]),"+f"(d[23]) : "r"(a0), "r"(a1), "r"(a2), "r"(a3), "l"(db), "r"(sd));
}
template<> __device__ __forceinline__ void wgmma_rs<64,0>(float* d, uint32_t a0, uint32_t a1, uint32_t a2, uint32_t a3, uint64_t db, int sd) {
  asm volatile("{\n.reg .pred p;\nsetp.ne.b32 p, %37, 0;\n"
  "wgmma.mma_async.sync.aligned.m64n64k16.f32.bf16.bf16 {%0,%1,%2,%3,%4,%5,%6,%7,%8,%9,%10,%11,%12,%13,%14,%15,%16,%17,%18,%19,%20,%21,%22,%23,%24,%25,%26,%27,%28,%29,%30,%31}, {%32,%33,%34,%35}, %36, p, 1, 1, 0;\n}\n"
  : "+f"(d[0]),"+f"(d[1]),"+f"(d[2]),"+f"(d[3]),"+f"(d[4]),"+f"(d[5]),"+f"(d[6]),"+f"(d[7]),"+f"(d[8]),"+f"(d[9]),"+f"(d[10]),"+f"(d[11]),"+f"(d[12]),"+f"(d[13]),"+f"(d[14]),"+f"(d[15]),"+f"(d[16]),"+f"(d[17]),"+f"(d[18]),"+f"(d[19]),"+f"(d[20]),"+f"(d[21]),"+f"(d[22]),"+f"(d[23]),"+f"(d[24]),"+f"(d[25]),"+f"(d[26]),"+f"(d[27]),"+f"(d[28]),"+f"(d[29]),"+f"(d[30]),"+f"(d[31]) : "r"(a0), "r"(a1), "r"(a2), "r"(a3), "l"(db), "r"(sd));
}
template<> __device__ __forceinline__ void wgmma_rs<80,0>(float* d, uint32_t a0, uint32_t a1, uint32_t a2, uint32_t a3, uint64_t db, int sd) {
  asm volatile("{\n.reg .pred p;\nsetp.ne.b32 p, %45, 0;\n"
  "wgmma.mma_async.sync.aligned.m64n80k16.f32.bf16.bf16 {%0,%1,%2,%3,%4,%5,%6,%7,%8,%9,%10,%11,%12,%13,%14,%15,%16,%17,%18,%19,%20,%21,%22,%23,%24,%25,%26,%27,%28,%29,%30,%31,%32,%33,%34,%35,%36,%37,%38,%39}, {%40,%41,%42,%43}, %44, p, 1, 1, 0;\n}\n"
  : "+f"(d[0]),"+f"(d[1]),"+f"(d[2]),"+f"(d[3]),"+f"(d[4]),"+f"(d[5]),"+f"(d[6]),"+f"(d[7]),"+f"(d[8]),"+f"(d[9]),"+f"(d[10]),"+f"(d[11]),"+f"(d[12]),"+f"(d[13]),"+f"(d[14]),"+f"(d[15]),"+f"(d[16]),"+f"(d[17]),"+f"(d[18]),"+f"(d[19]),"+f"(d[20]),"+f"(d[21]),"+f"(d[22]),"+f"(d[23]),"+f"(d[24]),"+f"(d[25]),"+f"(d[26]),"+f"(d[27]),"+f"(d[28]),"+f"(d[29]),"+f"(d[30]),"+f"(d[31]),"+f"(d[32]),"+f"(d[33]),"+f"(d[34]),"+f"(d[35]),"+f"(d[36]),"+f"(d[37]),"+f"(d[38]),"+f"(d[39]) : "r"(a0), "r"(a1), "r"(a2), "r"(a3), "l"(db), "r"(sd));
}
template<> __device__ __forceinline__ void wgmma_rs<96,0>(float* d, uint32_t a0, uint32_t a1, uint32_t a2, uint32_t a3, uint64_t db, int sd) {
  asm volatile("{\n.reg .pred p;\nsetp.ne.b32 p, %53, 0;\n"
  "wgmma.mma_async.sync.aligned.m64n96k16.f32.bf16.bf16 {%0,%1,%2,%3,%4,%5,%6,%7,%8,%9,%10,%11,%12,%13,%14,%15,%16,%17,%18,%19,%20,%21,%22,%23,%24,%25,%26,%27,%28,%29,%30,%31,%32,%33,%34,%35,%36,%37,%38,%39,%40,%41,%42,%43,%44,%45,%46,%47}, {%48,%49,%50,%51}, %52, p, 1, 1, 0;\n}\n"
  : "+f"(d[0]),"+f"(d[1]),"+f"(d[2]),"+f"(d[3]),"+f"(d[4]),"+f"(d[5]),"+f"(d[6]),"+f"(d[7]),"+f"(d[8]),"+f"(d[9]),"+f"(d[10]),"+f"(d[11]),"+f"(d[12]),"+f"(d[13]),"+f"(d[14]),"+f"(d[15]),"+f"(d[16]),"+f"(d[17]),"+f"(d[18]),"+f"(d[19]),"+f"(d[20]),"+f"(d[21]),"+f"(d[22]),"+f"(d[23]),"+f"(d[24]),"+f"(d[25]),"+f"(d[26]),"+f"(d[27]),"+f"(d[28]),"+f"(d[29]),"+f"(d[30]),"+f"(d[31]),"+f"(d[32]),"+f"(d[33]),"+f"(d[34]),"+f"(d[35]),"+f"(d[36]),"+f"(d[37]),"+f"(d[38]),"+f"(d[39]),"+f"(d[40]),"+f"(d[41]),"+f"(d[42]),"+f"(d[43]),"+f"(d[44]),"+f"(d[45]),"+f"(d[46]),"+f"(d[47]) : "r"(a0), "r"(a1), "r"(a2), "r"(a3), "l"(db), "r"(sd));
}
template<> __device__ __forceinline__ void wgmma_rs<112,0>(float* d, uint32_t a0, uint32_t a1, uint32_t a2, uint32_t a3, uint64_t db, int sd) {
  asm volatile("{\n.reg .pred p;\nsetp.ne.b32 p, %61, 0;\n"
  "wgmma.mma_async.sync.aligned.m64n112k16.f32.bf16.bf16 {%0,%1,%2,%3,%4,%5,%6,%7,%8,%9,%10,%11,%12,%13,%14,%15,%16,%17,%18,%19,%20,%21,%22,%23,%24,%25,%26,%27,%28,%29,%30,%31,%32,%33,%34,%35,%36,%37,%38,%39,%40,%41,%42,%43,%44,%45,%46,%47,%48,%49,%50,%51,%52,%53,%54,%55}, {%56,%57,%58,%59}, %60, p, 1, 1, 0;\n}\n"
  : "+f"(d[0]),"+f"(d[1]),"+f"(d[2]),"+f"(d[3]),"+f"(d[4]),"+f"(d[5]),"+f"(d[6]),"+f"(d[7]),"+f"(d[8]),"+f"(d[9]),"+f"(d[10]),"+f"(d[11]),"+f"(d[12]),"+f"(d[13]),"+f"(d[14]),"+f"(d[15]),"+f"(d[16]),"+f"(d[17]),"+f"(d[18]),"+f"(d[19]),"+f"(d[20]),"+f"(d[21]),"+f"(d[22]),"+f"(d[23]),"+f"(d[24]),"+f"(d[25]),"+f"(d[26]),"+f"(d[27]),"+f"(d[28]),"+f"(d[29]),"+f"(d[30]),"+f"(d[31]),"+f"(d[32]),"+f"(d[33]),"+f"(d[34]),"+f"(d[35]),"+f"(d[36]),"+f"(d[37]),"+f"(d[38]),"+f"(d[39]),"+f"(d[40]),"+f"(d[41]),"+f"(d[42]),"+f"(d[43]),"+f"(d[44]),"+f"(d[45]),"+f"(d[46]),"+f"(d[47]),"+f"(d[48]),"+f"(d[49]),"+f"(d[50]),"+f"(d[51]),"+f"(d[52]),"+f"(d[53]),"+f"(d[54]),"+f"(d[55]) : "r"(a0), "r"(a1), "r"(a2), "r"(a3), "l"(db), "r"(sd));
}
template<> __device__ __forceinline__ void wgmma_rs<128,0>(float* d, uint32_t a0, uint32_t a1, uint32_t a2, uint32_t a3, uint64_t db, int sd) {
  asm volatile("{\n.reg .pred p;\nsetp.ne.b32 p, %69, 0;\n"
  "wgmma.mma_async.sync.aligned.m64n128k16.f32.bf16.bf16 {%0,%1,%2,%3,%4,%5,%6,%7,%8,%9,%10,%11,%12,%13,%14,%15,%16,%17,%18,%19,%20,%21,%22,%23,%24,%25,%26,%27,%28,%29,%30,%31,%32,%33,%34,%35,%36,%37,%38,%39,%40,%41,%42,%43,%44,%45,%46,%47,%48,%49,%50,%51,%52,%53,%54,%55,%56,%57,%58,%59,%60,%61,%62,%63}, {%64,%65,%66,%67}, %68, p, 1, 1, 0;\n}\n"
  : "+f"(d[0]),"+f"(d[1]),"+f"(d[2]),"+f"(d[3]),"+f"(d[4]),"+f"(d[5]),"+f"(d[6]),"+f"(d[7]),"+f"(d[8]),"+f"(d[9]),"+f"(d[10]),"+f"(d[11]),"+f"(d[12]),"+f"(d[13]),"+f"(d[14]),"+f"(d[15]),"+f"(d[16]),"+f"(d[17]),"+f"(d[18]),"+f"(d[19]),"+f"(d[20]),"+f"(d[21]),"+f"(d[22]),"+f"(d[23]),"+f"(d[24]),"+f"(d[25]),"+f"(d[26]),"+f"(d[27]),"+f"(d[28]),"+f"(d[29]),"+f"(d[30]),"+f"(d[31]),"+f"(d[32]),"+f"(d[33]),"+f"(d[34]),"+f"(d[35]),"+f"(d[36]),"+f"(d[37]),"+f"(d[38]),"+f"(d[39]),"+f"(d[40]),"+f"(d[41]),"+f"(d[42]),"+f"(d[43]),"+f"(d[44]),"+f"(d[45]),"+f"(d[46]),"+f"(d[47]),"+f"(d[48]),"+f"(d[49]),"+f"(d[50]),"+f"(d[51]),"+f"(d[52]),"+f"(d[53]),"+f"(d[54]),"+f"(d[55]),"+f"(d[56]),"+f"(d[57]),"+f"(d[58]),"+f"(d[59]),"+f"(d[60]),"+f"(d[61]),"+f"(d[62]),"+f"(d[63]) : "r"(a0), "r"(a1), "r"(a2), "r"(a3), "l"(db), "r"(sd));
}

namespace {
typedef __nv_bfloat16 bf16;
constexpr int SB0      = 1024;
constexpr int OFF_S    = 1024;
constexpr int STG      = 49152;
constexpr int STG_TX   = 47104;
constexpr int OFF_PHIK = OFF_S - 128;
constexpr int PHIK_HS  = 10240 + 32;
constexpr int OFF_VB   = OFF_S + 49152;
constexpr int OFF_WO   = OFF_S + 75776;
constexpr int OFF_WOT  = OFF_S + 126976;
constexpr int OFF_PHI  = OFF_S + 147456;
constexpr int OFF_KVB  = OFF_PHI + 12800;
constexpr int KVB_S    = 2592;
constexpr int OFF_U    = OFF_KVB + 28672;
constexpr int OFF_KT   = OFF_U + 8960;
constexpr int OFF_P    = OFF_KT + 16640;
constexpr int OFF_G    = 256;
constexpr int OFF_KX   = OFF_S + 40960;
constexpr int SMEM_BYTES = OFF_P + 16384;
static_assert(SMEM_BYTES <= 232448, "smem");
constexpr int B_FULL = 0, B_EMPTY = 24, B_FULLO = 48, B_EMPTYO = 80, B_WO = 112, B_Y = 120, B_FULLU = 128, B_Z = 152, B_T = 160, B_KX = 168;
constexpr int C_X = 0, C_Y = 8, C_KV = 16, C_O = 40, C_DONE = 56, C_NUM = 64;

struct Scratch {
  unsigned char xT[640 * 4096];
  unsigned char y[16 * 640 * 256];
  unsigned char o[16 * 8 * 20480];
  float kv[8 * 2 * 2560];
  float gate[16 * 128];
  unsigned cnt[C_NUM * 32];
};
__device__ __align__(1024) Scratch g_s;
#define STAMPM(i)
#define STAMP(i)
#define STAMPW(i)

#define KUNR_S "unroll 1"
constexpr int SPIN_MAX = 1 << 22;
__device__ __forceinline__ uint32_t smem_u32(const void* p) { return (uint32_t)__cvta_generic_to_shared(p); }
__device__ __forceinline__ void mbar_init(uint32_t bar, int cnt) { asm volatile("mbarrier.init.shared::cta.b64 [%0], %1;" ::"r"(bar), "r"(cnt)); }
__device__ __forceinline__ void mbar_expect(uint32_t bar, int bytes) { asm volatile("mbarrier.arrive.expect_tx.shared::cta.b64 _, [%0], %1;" ::"r"(bar), "r"(bytes) : "memory"); }
__device__ __forceinline__ void mbar_arrive(uint32_t bar) { asm volatile("mbarrier.arrive.shared::cta.b64 _, [%0];" ::"r"(bar) : "memory"); }
__device__ __forceinline__ void mbar_arrive_cl(uint32_t bar, uint32_t cta) {
  asm volatile("{\n.reg .b32 ra;\nmapa.shared::cluster.u32 ra, %0, %1;\nmbarrier.arrive.shared::cluster.b64 _, [ra];\n}\n" ::"r"(bar), "r"(cta) : "memory");
}
__device__ __forceinline__ bool mbar_try(uint32_t bar, int parity) {
  uint32_t ok;
  asm volatile("{\n.reg .pred p;\nmbarrier.try_wait.parity.shared::cta.b64 p, [%1], %2;\nselp.u32 %0, 1, 0, p;\n}\n" : "=r"(ok) : "r"(bar), "r"(parity) : "memory");
  return ok;
}
__device__ __forceinline__ bool mbar_test(uint32_t bar, int parity) {
  uint32_t ok;
  asm volatile("{\n.reg .pred p;\nmbarrier.test_wait.parity.shared::cta.b64 p, [%1], %2;\nselp.u32 %0, 1, 0, p;\n}\n" : "=r"(ok) : "r"(bar), "r"(parity) : "memory");
  return ok;
}
__device__ __forceinline__ void mbar_wait(uint32_t bar, int parity) {
  int n = 0;
  while (!mbar_try(bar, parity)) { if (++n > SPIN_MAX) __trap(); }
}
__device__ __forceinline__ void mbar_wait_nt(uint32_t bar, int parity) {
  int n = 0;
  while (!mbar_try(bar, parity) && ++n < SPIN_MAX) {}
}
__device__ __forceinline__ unsigned ld_acq(const unsigned* p) { unsigned v; asm volatile("ld.acquire.gpu.global.u32 %0, [%1];" : "=r"(v) : "l"(p) : "memory"); return v; }
__device__ __forceinline__ void poll(const unsigned* p, unsigned target) {
  int n = 0;
  while ((int)(ld_acq(p) - target) < 0) { if (++n > SPIN_MAX) __trap(); }
}
__device__ __forceinline__ void red_rel(unsigned* p) { asm volatile("red.release.gpu.global.add.u32 [%0], 1;" ::"l"(p) : "memory"); }
__device__ __forceinline__ void red_rlx(unsigned* p) { asm volatile("red.relaxed.gpu.global.add.u32 [%0], 1;" ::"l"(p) : "memory"); }
__device__ __forceinline__ void fence_async() { asm volatile("fence.proxy.async.shared::cta;" ::: "memory"); }
__device__ __forceinline__ void fence_async_g() { asm volatile("fence.proxy.async.global;" ::: "memory"); }
__device__ __forceinline__ void bar_sync(int id, int n) { asm volatile("bar.sync %0, %1;" ::"r"(id), "r"(n) : "memory"); }
__device__ __forceinline__ void bar_arrive(int id, int n) { asm volatile("bar.arrive %0, %1;" ::"r"(id), "r"(n) : "memory"); }
__device__ __forceinline__ void wg_fence() { asm volatile("wgmma.fence.sync.aligned;" ::: "memory"); }
__device__ __forceinline__ void wg_commit() { asm volatile("wgmma.commit_group.sync.aligned;" ::: "memory"); }
template <int N> __device__ __forceinline__ void wg_wait() { asm volatile("wgmma.wait_group.sync.aligned %0;" ::"n"(N) : "memory"); }
template <int N> __device__ __forceinline__ void reg_fence(float* d) {
#pragma unroll
  for (int i = 0; i < N; i++) asm volatile("" : "+f"(d[i])::"memory");
}
template <int N> __device__ __forceinline__ void reg_fence(uint32_t* d) {
#pragma unroll
  for (int i = 0; i < N; i++) asm volatile("" : "+r"(d[i])::"memory");
}
__device__ __forceinline__ uint64_t mkdesc(uint32_t addr, uint32_t lbo, uint32_t sbo, uint32_t swz) {
  return (uint64_t)((addr >> 4) & 0x3FFF) | ((uint64_t)(lbo >> 4) << 16) | ((uint64_t)(sbo >> 4) << 32) | ((uint64_t)swz << 62);
}
__device__ __forceinline__ uint32_t pack(float lo, float hi) { uint32_t r; asm("cvt.rn.bf16x2.f32 %0, %1, %2;" : "=r"(r) : "f"(hi), "f"(lo)); return r; }
__device__ __forceinline__ float blo(uint32_t v) { return __uint_as_float(v << 16); }
__device__ __forceinline__ float bhi(uint32_t v) { return __uint_as_float(v & 0xFFFF0000u); }
__device__ __forceinline__ float ex2(float x) { float r; asm("ex2.approx.ftz.f32 %0, %1;" : "=f"(r) : "f"(x)); return r; }
__device__ __forceinline__ float rcp(float x) { float r; asm("rcp.approx.ftz.f32 %0, %1;" : "=f"(r) : "f"(x)); return r; }
__device__ __forceinline__ void sts32(uint32_t a, uint32_t v) { asm volatile("st.shared.u32 [%0], %1;" ::"r"(a), "r"(v) : "memory"); }
__device__ __forceinline__ void sts128(uint32_t a, uint32_t x, uint32_t y, uint32_t z, uint32_t w) { asm volatile("st.shared.v4.u32 [%0], {%1,%2,%3,%4};" ::"r"(a), "r"(x), "r"(y), "r"(z), "r"(w) : "memory"); }
__device__ __forceinline__ uint32_t lds32(uint32_t a) { uint32_t v; asm volatile("ld.shared.u32 %0, [%1];" : "=r"(v) : "r"(a) : "memory"); return v; }
__device__ __forceinline__ uint32_t lds16(uint32_t a) { uint16_t v; asm volatile("ld.shared.u16 %0, [%1];" : "=h"(v) : "r"(a) : "memory"); return v; }
__device__ __forceinline__ uint4 lds128(uint32_t a) { uint4 v; asm volatile("ld.shared.v4.u32 {%0,%1,%2,%3}, [%4];" : "=r"(v.x), "=r"(v.y), "=r"(v.z), "=r"(v.w) : "r"(a) : "memory"); return v; }
__device__ __forceinline__ float4 lds128f(uint32_t a) { float4 v; asm volatile("ld.shared.v4.f32 {%0,%1,%2,%3}, [%4];" : "=f"(v.x), "=f"(v.y), "=f"(v.z), "=f"(v.w) : "r"(a) : "memory"); return v; }
__device__ __forceinline__ void stsm4(uint32_t a, uint32_t r0, uint32_t r1, uint32_t r2, uint32_t r3) { asm volatile("stmatrix.sync.aligned.m8n8.x4.shared.b16 [%0], {%1,%2,%3,%4};" ::"r"(a), "r"(r0), "r"(r1), "r"(r2), "r"(r3) : "memory"); }
__device__ __forceinline__ void stsm4t(uint32_t a, uint32_t r0, uint32_t r1, uint32_t r2, uint32_t r3) { asm volatile("stmatrix.sync.aligned.m8n8.x4.trans.shared.b16 [%0], {%1,%2,%3,%4};" ::"r"(a), "r"(r0), "r"(r1), "r"(r2), "r"(r3) : "memory"); }
__device__ __forceinline__ uint4 ldsm4t(uint32_t a) { uint4 v; asm volatile("ldmatrix.sync.aligned.m8n8.x4.trans.shared.b16 {%0,%1,%2,%3}, [%4];" : "=r"(v.x), "=r"(v.y), "=r"(v.z), "=r"(v.w) : "r"(a) : "memory"); return v; }
__device__ __forceinline__ void tma2d(uint32_t dst, const CUtensorMap* m, int c0, int c1, uint32_t bar) {
  asm volatile("cp.async.bulk.tensor.2d.shared::cluster.global.mbarrier::complete_tx::bytes [%0], [%1, {%3,%4}], [%2];" ::"r"(dst), "l"(m), "r"(bar), "r"(c0), "r"(c1) : "memory");
}
__device__ __forceinline__ void tma3d_mc(uint32_t dst, const CUtensorMap* m, int c0, int c1, int c2, uint32_t bar) {
  asm volatile("cp.async.bulk.tensor.3d.shared::cluster.global.mbarrier::complete_tx::bytes.multicast::cluster [%0], [%1, {%3,%4,%5}], [%2], %6;" ::"r"(dst), "l"(m), "r"(bar), "r"(c0), "r"(c1), "r"(c2), "h"((uint16_t)3) : "memory");
}
__device__ __forceinline__ void tma5d(uint32_t dst, const CUtensorMap* m, int c0, int c1, int c2, int c3, int c4, uint32_t bar) {
  asm volatile("cp.async.bulk.tensor.5d.shared::cluster.global.mbarrier::complete_tx::bytes [%0], [%1, {%3,%4,%5,%6,%7}], [%2];" ::"r"(dst), "l"(m), "r"(bar), "r"(c0), "r"(c1), "r"(c2), "r"(c3), "r"(c4) : "memory");
}
__device__ __forceinline__ void bulk_ld(uint32_t dst, const void* src, int bytes, uint32_t bar) {
  asm volatile("cp.async.bulk.shared::cluster.global.mbarrier::complete_tx::bytes [%0], [%1], %2, [%3];" ::"r"(dst), "l"(src), "r"(bytes), "r"(bar) : "memory");
}
__device__ __forceinline__ void bulk_ld_mc(uint32_t dst, const void* src, int bytes, uint32_t bar) {
  asm volatile("cp.async.bulk.shared::cluster.global.mbarrier::complete_tx::bytes.multicast::cluster [%0], [%1], %2, [%3], %4;" ::"r"(dst), "l"(src), "r"(bytes), "r"(bar), "h"((uint16_t)3) : "memory");
}
__device__ __forceinline__ void tma_st2d(const CUtensorMap* m, uint32_t src, int c0, int c1) {
  asm volatile("cp.async.bulk.tensor.2d.global.shared::cta.bulk_group [%0, {%2,%3}], [%1];" ::"l"(m), "r"(src), "r"(c0), "r"(c1) : "memory");
}
__device__ __forceinline__ void red4(float* p, float a, float b, float c) { asm volatile("red.relaxed.gpu.global.add.v4.f32 [%0], {%1,%2,%3,%4};" ::"l"(p), "f"(a), "f"(b), "f"(c), "f"(1.f) : "memory"); }
__device__ __forceinline__ float4 ld_rlx4(const float* p) { float4 v; asm volatile("ld.relaxed.gpu.global.v4.f32 {%0,%1,%2,%3}, [%4];" : "=f"(v.x), "=f"(v.y), "=f"(v.z), "=f"(v.w) : "l"(p) : "memory"); return v; }
__device__ __forceinline__ unsigned ld_rlx(const unsigned* p) { unsigned v; asm volatile("ld.relaxed.gpu.global.u32 %0, [%1];" : "=r"(v) : "l"(p) : "memory"); return v; }
__device__ __forceinline__ uint32_t mapa(uint32_t a, uint32_t cta) { uint32_t r; asm("mapa.shared::cluster.u32 %0, %1, %2;" : "=r"(r) : "r"(a), "r"(cta)); return r; }
__device__ __forceinline__ void st_async4(uint32_t a, float x, float y, float z, float w, uint32_t bar) {
  asm volatile("st.async.weak.shared::cluster.mbarrier::complete_tx::bytes.v4.f32 [%0], {%1,%2,%3,%4}, [%5];" ::"r"(a), "f"(x), "f"(y), "f"(z), "f"(w), "r"(bar) : "memory");
}
__device__ __forceinline__ void cl_arrive() { asm volatile("barrier.cluster.arrive.relaxed.aligned;" ::: "memory"); }
__device__ __forceinline__ void cl_wait() { asm volatile("barrier.cluster.wait.acquire.aligned;" ::: "memory"); }
__device__ __forceinline__ float bf2f(uint16_t v) { return __uint_as_float((uint32_t)v << 16); }
__device__ __forceinline__ float rbf(float x) { return __bfloat162float(__float2bfloat16_rn(x)); }

__device__ __forceinline__ void softmax2(const float* p, uint32_t* ph0, uint32_t* ph1) {
  constexpr float L = 1.4426950408889634f;
#pragma unroll
  for (int r = 0; r < 2; r++) {
    uint32_t* ph = r ? ph1 : ph0;
    float mx = fmaxf(p[2 * r], p[2 * r + 1]), mn = fminf(p[2 * r], p[2 * r + 1]);
#pragma unroll
    for (int j = 1; j < 10; j++) {
      mx = fmaxf(mx, fmaxf(p[4 * j + 2 * r], p[4 * j + 2 * r + 1]));
      mn = fminf(mn, fminf(p[4 * j + 2 * r], p[4 * j + 2 * r + 1]));
    }
    const float mxl = -mx * L, mnl = mn * L;
    float e[20], s0 = 0.f, s1 = 0.f;
#pragma unroll
    for (int j = 0; j < 10; j++) {
      e[2 * j] = ex2(fmaf(p[4 * j + 2 * r], L, mxl));
      e[2 * j + 1] = ex2(fmaf(p[4 * j + 2 * r + 1], L, mxl));
      s0 += e[2 * j]; s1 += e[2 * j + 1];
    }
    float rs = rcp(s0 + s1);
#pragma unroll
    for (int j = 0; j < 10; j++) ph[j] = pack(e[2 * j] * rs, e[2 * j + 1] * rs);
    s0 = 0.f; s1 = 0.f;
#pragma unroll
    for (int j = 0; j < 10; j++) {
      e[2 * j] = ex2(fmaf(p[4 * j + 2 * r], -L, mnl));
      e[2 * j + 1] = ex2(fmaf(p[4 * j + 2 * r + 1], -L, mnl));
      s0 += e[2 * j]; s1 += e[2 * j + 1];
    }
    rs = rcp(s0 + s1);
#pragma unroll
    for (int j = 0; j < 10; j++) ph[10 + j] = pack(e[2 * j] * rs, e[2 * j + 1] * rs);
  }
}

struct cf { float x, y; };
__device__ __forceinline__ cf cexpp(float a2, float be, float p) {
  float m = ex2(a2 * p), th = be * p;
  return cf{m * __cosf(th), m * __sinf(th)};
}
__device__ __forceinline__ cf cmul(cf a, cf b) { return cf{fmaf(a.x, b.x, -a.y * b.y), fmaf(a.x, b.y, a.y * b.x)}; }

template <int SH> __device__ __forceinline__ void expand16(uint32_t kv, int base, uint32_t dst) {
  constexpr int NV = (16 >> SH) + 1;
  uint32_t v[NV];
#pragma unroll
  for (int i = 0; i < NV; i++) v[i] = (SH == 0 && i == 0) ? 0u : lds16(kv + 2 * (base + i));
  uint32_t w[8];
#pragma unroll
  for (int i = 0; i < 8; i++) {
    int q[2];
#pragma unroll
    for (int h = 0; h < 2; h++) {
      int e = 16 - (2 * i + h);
      int qq = e >> SH, rem = e & ((1 << SH) - 1), half = (1 << SH) >> 1;
      if (SH > 0 && (rem > half || (rem == half && (qq & 1)))) qq++;
      q[h] = qq;
    }
    w[i] = v[q[0]] | (v[q[1]] << 16);
  }
  sts128(dst, w[0], w[1], w[2], w[3]);
  sts128(dst + 16, w[4], w[5], w[6], w[7]);
}

__device__ __forceinline__ uint32_t prmt(uint32_t a, uint32_t b, uint32_t s) { uint32_t r; asm("prmt.b32 %0, %1, %2, %3;" : "=r"(r) : "r"(a), "r"(b), "r"(s)); return r; }
__host__ __device__ constexpr int cstep(int p) { return p; }
template <int P> __device__ __forceinline__ void conv_raw(uint32_t ka, uint32_t* a) {
#pragma unroll
  for (int h = 0; h < 2; h++) {
    const uint32_t ad = ka - 128 * (2 * cstep(P & 15) + h) - (P >> 4) * 4160;
    a[4 * h + 1] = lds32(ad - 4); a[4 * h + 0] = lds32(ad); a[4 * h + 2] = lds32(ad + 4);
  }
}
__device__ __forceinline__ void conv_perm(uint32_t* c) {
  uint32_t sel;
  asm volatile("mov.u32 %0, %%clock;" : "=r"(sel) :: "memory");
  sel = sel * 65536u + 0x5432u;
  c[1] = prmt(c[1], c[0], sel); c[3] = prmt(c[0], c[2], sel);
  c[5] = prmt(c[5], c[4], sel); c[7] = prmt(c[4], c[6], sel);
  reg_fence<8>(c);
}
template <int P> struct ConvLoop {
  static __device__ __forceinline__ void run(float* acc, uint32_t ka, uint64_t db, uint32_t (*a)[8]) {
    constexpr int G = cstep(P);
    uint32_t* c = a[P & 3];
    wg_fence();
    wgmma_rs<128 - 16 * (G / 2), 0>(acc, c[0], c[1], c[2], c[3], db + 8 * G, 1);
    wgmma_rs<128 - 16 * (G / 2), 0>(acc, c[4], c[5], c[6], c[7], db + 8 * G + 4, 1);
    wg_commit();
    conv_raw<P + 2>(ka, a[(P + 2) & 3]);
    conv_perm(a[(P + 1) & 3]);
    wg_wait<1>();
    ConvLoop<P + 1>::run(acc, ka, db, a);
  }
};
template <> struct ConvLoop<16> { static __device__ __forceinline__ void run(float*, uint32_t, uint64_t, uint32_t (*)[8]) {} };

__device__ __forceinline__ cf csq(cf a) { return cf{fmaf(a.x, a.x, -a.y * a.y), (a.x + a.x) * a.y}; }
__device__ __forceinline__ void sts16(uint32_t a, uint32_t v) { asm volatile("st.shared.u16 [%0], %1;" ::"r"(a), "h"((uint16_t)v) : "memory"); }

struct Params {
  Scratch* s;
  const uint16_t *wo, *lar, *aim, *cre, *cim, *ldt, *dsk;
  const uint32_t* wphi;
  const uint4 *gw, *x, *w;
};

__global__ void __cluster_dims__(2, 1, 1) __launch_bounds__(512, 1)
fused_kernel(const __grid_constant__ Params prm, const __grid_constant__ CUtensorMap tmX, const __grid_constant__ CUtensorMap tmW,
             const __grid_constant__ CUtensorMap tmWt, const __grid_constant__ CUtensorMap tmWo,
             const __grid_constant__ CUtensorMap tmOut) {
  extern __shared__ __align__(1024) unsigned char smem_raw[];
  const uint32_t sb = smem_u32(smem_raw);
  const int tid = threadIdx.x, lane = tid & 31;
  const int warp = __shfl_sync(0xffffffffu, tid >> 5, 0);
  const int g = lane >> 2, t = lane & 3;
  const int cta = blockIdx.x, rank = cta & 1, cl = cta >> 1;
  const int cg = cl & 7, rt = 2 * (cl >> 3) + rank;
  const int rt3 = 2 * (cl >> 3) + (cg & 1), ct3 = (cg & 6) + rank;
  unsigned* const cnt = prm.s->cnt;
  const int wgid = warp >> 2, th = tid & 127;
  uint16_t n_lar, n_aim, n_cre, n_cim, n_ldt, n_dsk;
  auto kload = [&](int j) {
    const int q = cta * 640 + 128 * j + th;
    n_lar = __ldg(prm.lar + q); n_aim = __ldg(prm.aim + q); n_cre = __ldg(prm.cre + q); n_cim = __ldg(prm.cim + q);
    n_ldt = __ldg(prm.ldt + 5 * cta + j); n_dsk = __ldg(prm.dsk + 5 * cta + j);
  };
  if (wgid >= 2) kload(wgid - 2);

  if (warp == 12) {
    if (lane == 0) {
      mbar_init(sb + B_FULL, 1);
      asm volatile("fence.mbarrier_init.release.cluster;" ::: "memory");
    }
    __syncwarp();
    cl_arrive();
    STAMPW(110);
    if (lane == 0) {
      mbar_expect(sb + B_FULL, STG_TX);
      tma2d(sb + OFF_S, &tmX, 0, 128 * rt, sb + B_FULL);
      STAMP(113);
    }
    __syncwarp();
    STAMPW(111);
  } else if (warp == 13) {
    if (lane == 0) {
      if ((sb & 0xFFFFFF) != SB0) __trap();
      asm volatile("prefetch.tensormap [%0];" ::"l"(&tmW) : "memory");
      asm volatile("prefetch.tensormap [%0];" ::"l"(&tmWt) : "memory");
      mbar_init(sb + B_FULL + 8, 1); mbar_init(sb + B_FULL + 16, 1);
      for (int i = 0; i < 3; i++) mbar_init(sb + B_EMPTY + 8 * i, 16);
      for (int i = 0; i < 4; i++) { mbar_init(sb + B_FULLO + 8 * i, 1); mbar_init(sb + B_EMPTYO + 8 * i, 16); }
      mbar_init(sb + B_WO, 4); mbar_init(sb + B_Y, 1); mbar_init(sb + B_FULLU, 1); mbar_init(sb + B_FULLU + 8, 1);
      mbar_init(sb + B_Z, 5); mbar_init(sb + B_T, 1); mbar_init(sb + B_KX, 1);
      asm volatile("fence.mbarrier_init.release.cluster;" ::: "memory");
    }
    __syncwarp();
    cl_arrive();
    cl_wait();
    STAMPW(112);
    if (lane == 0) {
      tma3d_mc(sb + OFF_S + 16384 + rank * 16384, &tmW, 80 * cg, 32 * rank, 0, sb + B_FULL);
      tma3d_mc(sb + OFF_S + 16384 + rank * 16384 + 12288, &tmWt, 80 * cg + 64, 32 * rank, 0, sb + B_FULL);
      for (int kb = 1; kb < 3; kb++) {
        const uint32_t st = sb + OFF_S + (3 - kb) * STG, bar = sb + B_FULL + 8 * kb;
        mbar_expect(bar, STG_TX);
        tma2d(st, &tmX, 64 * kb, 128 * rt, bar);
        tma3d_mc(st + 16384 + rank * 16384, &tmW, 80 * cg, 64 * kb + 32 * rank, 0, bar);
        tma3d_mc(st + 16384 + rank * 16384 + 12288, &tmWt, 80 * cg + 64, 64 * kb + 32 * rank, 0, bar);
      }
      mbar_expect(sb + B_KX, 7680);
    }
    __syncwarp();
    STAMPW(64);
  } else {
    cl_arrive();
  }

  if (wgid >= 2) {
    const uint32_t sa = sb + (wgid == 3 ? OFF_P : OFF_KVB);
    const uint32_t sq = sb + (wgid == 3 ? OFF_KT : OFF_KVB + 16384);
    uint32_t kv = sb + OFF_U + (wgid - 2) * 2240;
    const uint32_t ea = ((th & 63) >> 3) * 256 + (th & 7) * 16;
#pragma unroll 1
    for (int pass = 0;; pass++) {
      const float dt = rbf(expf(bf2f(n_ldt))), dsk = bf2f(n_dsk);
      const float a2 = -rbf(expf(bf2f(n_lar))) * dt * 1.4426950408889634f, be = bf2f(n_aim) * dt;
      cf S = cf{2.f * (bf2f(n_cre) * dt), -2.f * (bf2f(n_cim) * dt)};
      if (wgid == 2 && pass < 3) kload(pass + 2);
      cf z[9];
      z[1] = cexpp(a2, be, 1.f);
      const cf z64 = cexpp(a2, be, 64.f);
      z[2] = csq(z[1]); z[3] = cmul(z[2], z[1]); z[4] = csq(z[2]);
      z[5] = cmul(z[4], z[1]); z[6] = csq(z[3]); z[7] = cmul(z[4], z[3]); z[8] = csq(z[4]);
      const uint32_t ba = sq + ea + (th >> 6) * 6144;
      sts128(ba, pack(1.f, z[1].x), pack(z[2].x, z[3].x), pack(z[4].x, z[5].x), pack(z[6].x, z[7].x));
      sts128(ba + 128, pack(0.f, z[1].y), pack(z[2].y, z[3].y), pack(z[4].y, z[5].y), pack(z[6].y, z[7].y));
      {
        const cf z256 = csq(csq(z64)), z512 = csq(z256), z768 = cmul(z512, z256), z1024 = csq(z512);
        const cf a = cmul(z256, z[2]), b = cmul(z256, z[4]), c = cmul(z256, z[6]), d = cmul(z512, z[4]), f = cmul(z768, z[4]);
        sts128(ba + 2048, pack(z256.x, a.x), pack(b.x, c.x), pack(z512.x, d.x), pack(z768.x, f.x));
        sts128(ba + 2048 + 128, pack(z256.y, a.y), pack(b.y, c.y), pack(z512.y, d.y), pack(z768.y, f.y));
        const cf p = cmul(z1024, z256), q = csq(z768), r = cmul(z1024, z768), u = csq(z1024);
        sts128(ba + 4096, pack(z1024.x, p.x), pack(q.x, r.x), pack(u.x, 0.f), 0);
        sts128(ba + 4096 + 128, pack(z1024.y, p.y), pack(q.y, r.y), pack(u.y, 0.f), 0);
      }
      cf T[8];
      T[1] = cf{z[8].x, -z[8].y}; T[2] = csq(T[1]); T[3] = cmul(T[2], T[1]); T[4] = csq(T[2]);
      T[5] = cmul(T[4], T[1]); T[6] = csq(T[3]); T[7] = cmul(T[4], T[3]);
      uint32_t aa = sa + ea + (th >> 6) * 2048;
      _Pragma(KUNR_S)
      for (int c = 0; c < 4; c++) {
        cf v[8];
        v[0] = S;
#pragma unroll
        for (int r = 1; r < 8; r++) v[r] = cmul(S, T[r]);
        S = cmul(S, cf{z64.x, -z64.y});
        sts128(aa, pack(v[0].x, v[1].x), pack(v[2].x, v[3].x), pack(v[4].x, v[5].x), pack(v[6].x, v[7].x));
        sts128(aa + 128, pack(v[0].y, v[1].y), pack(v[2].y, v[3].y), pack(v[4].y, v[5].y), pack(v[6].y, v[7].y));
        aa += 4096;
      }
      if ((warp & 3) == 0 && pass == 0) STAMPW(224 + wgid);
      fence_async();
      bar_sync(7 + wgid, 128);
      float kc[24];
      const uint64_t da = mkdesc(sa, 128, 2048, 0), db = mkdesc(sq, 128, 2048, 0);
      wg_fence();
#pragma unroll
      for (int s = 0; s < 8; s++) wgmma_ss<48, 1, 1>(kc, da + 16 * s, db + 16 * s, s > 0);
      wg_commit();
      if (pass == 0 && warp != 13) cl_wait();
      wg_wait<0>();
      reg_fence<24>(kc);
      {
        const int i = th >> 2;
        sts32(kv + (8 * i + 2 * t) * 2, pack(kc[0] + kc[14] + (th == 0 ? dsk : 0.f), kc[1] + kc[15]));
        sts32(kv + (t < 2 ? 256 + 4 * i + 2 * t : 256 + 64 * t + 2 * i) * 2, pack(kc[4] + kc[18], kc[5] + kc[19]));
        const uint32_t u = pack(kc[8] + kc[22], kc[9] + kc[23]);
        if (t < 2 || th == 2) sts16(kv + (512 + 64 * t + i) * 2, u);
        if (t < 2) sts16(kv + (544 + 64 * t + i) * 2, u >> 16);
      }
      if ((warp & 3) == 0) STAMPW(228 + wgid + 4 * pass);
      if (wgid == 3) break;
      bar_sync(4, 128);
      bar_arrive(11 + pass, 192);
      if (pass == 3) break;
      kv = sb + (pass < 2 ? OFF_U + (pass + 2) * 2240 : OFF_P + 4160);
    }
  }

  if (warp < 8) {
    const int wg = warp >> 2, w = warp & 3;
    {
      uint32_t wv[4];
#pragma unroll
      for (int i = 0; i < 4; i++) { int idx = tid + 256 * i; wv[i] = idx < 800 ? __ldg(prm.wphi + cg * 800 + idx) : 0u; }
#pragma unroll
      for (int i = 0; i < 4; i++) {
        const int idx = tid + 256 * i, kk = idx / 10, j = idx - kk * 10, h = kk / 20;
        if (idx < 800) sts128(sb + OFF_PHI + j * 1280 + kk * 16, h == 0 ? wv[i] : 0u, h == 1 ? wv[i] : 0u, h == 2 ? wv[i] : 0u, h == 3 ? wv[i] : 0u);
      }
      fence_async();
      cl_wait();
    }
    uint32_t raA, raB;
    uint32_t oA, oB;
    {
      const int tt = (lane >> 1) & 3, row = 64 * ((warp >> 1) & 1) + 16 * tt + 4 * (lane >> 3) + 2 * wg + (lane & 1);
      const int sA = cg < 3 ? cg : 0, sB = cg < 3 ? 0 : 1;
      raA = sb + OFF_S + ((3 - sA) % 3) * STG + row * 128 + (((warp & 1) ^ (2 * tt) ^ (row & 7)) * 16);
      oA = ((64 * cg + 8 * (warp & 1) + g) * 4096 + wg * 2048 + (127 - 8 * rt - 4 * ((warp >> 1) & 1) - t) * 16);
      const int rowb = 32 * (cg & 3) + 16 * (tt & 1) + 4 * (lane >> 3) + (tt & 2) + (lane & 1);
      raB = sb + OFF_S + sB * 2 * STG + rowb * 128 + ((warp ^ (rowb & 7)) * 16);
      oB = ((512 + 64 * (cg >> 2) + 8 * warp + g) * 4096 + (t >> 1) * 2048 + (127 - 8 * rt - 2 * (cg & 3) - (t & 1)) * 16);
      asm volatile("" : "+r"(raA), "+r"(raB), "+r"(oA), "+r"(oB));
    }
    asm volatile("setmaxnreg.inc.sync.aligned.u32 168;");
    {
    int lane;
    asm volatile("mov.u32 %0, %%laneid;" : "=r"(lane));
    const int g = lane >> 2, t = lane & 3;
    float acc[120];
#pragma unroll
    for (int i = 0; i < 120; i++) acc[i] = 0.f;
    reg_fence<120>(acc);
    STAMPW(0 + warp);
    int pA = cg < 3 ? cg : 3, pB = cg < 3 ? 3 : 4;
    asm volatile("" : "+r"(pA), "+r"(pB));
    const uint32_t eb = mapa(sb + B_EMPTY, lane & 1);
    uint32_t so = 0, fb = sb + B_FULL, par = 0, eo = 16;
    const uint32_t la0 = ((SB0 + OFF_S) >> 4) + (1 << 16) + wg * 512;
#pragma unroll 1
    for (int kb = 0; kb < 10; kb++) {
      bool rel = kb > 0 && lane < 2;
      if (!__all_sync(0xffffffffu, mbar_test(fb, par))) {
        wg_wait<0>();
        if (rel) asm volatile("mbarrier.arrive.shared::cluster.b64 _, [%0];" ::"r"(eb + eo) : "memory");
        rel = false;
        mbar_wait_nt(fb, par);
      }
      if (warp == 0) STAMPM(40 + kb);
      if (warp == 4) STAMPM(130 + kb);
      const uint64_t da = 0x4000004000000000ull | (la0 + so);
      const uint64_t db = 0x4000004000000000ull | (((SB0 + OFF_S + 16384) >> 4) + (256 << 16) + so);
      const uint64_t dt = 0xC000001000000000ull | (((SB0 + OFF_S + 28672) >> 4) + (64 << 16) + so);
      wg_fence();
#pragma unroll
      for (int ks = 0; ks < 2; ks++) {
        wgmma_ss<192, 0, 1>(acc, da + 2 * ks, db + ks * 128, 1);
        wgmma_ss<48, 0, 1>(acc + 96, da + 2 * ks, dt + ks * 32, 1);
      }
      wg_commit();
      wg_wait<1>();
      if (rel) asm volatile("mbarrier.arrive.shared::cluster.b64 _, [%0];" ::"r"(eb + eo) : "memory");
      if (w == 0) STAMPM(159 + 10 * wg + kb);
      wg_fence();
#pragma unroll
      for (int ks = 0; ks < 2; ks++) {
        wgmma_ss<192, 0, 1>(acc, da + 4 + 2 * ks, db + 1024 + ks * 128, 1);
        wgmma_ss<48, 0, 1>(acc + 96, da + 4 + 2 * ks, dt + 1024 + ks * 32, 1);
      }
      wg_commit();
      if (w == 0) STAMPM(140 + 10 * wg + kb);
      if (so == STG / 16) { fb -= 16; par ^= 1; } else fb += 8;
      eo = eo == 16 ? 0 : eo + 8;
      so = so == 0 ? 2 * STG / 16 : so - STG / 16;
      if (kb == pA) {
        uint4 v0 = ldsm4t(raA), v1 = ldsm4t(raA ^ 32), v2 = ldsm4t(raA ^ 64), v3 = ldsm4t(raA ^ 96);
        if (t & 1) { uint4 u = v0; v0 = v1; v1 = u; u = v2; v2 = v3; v3 = u; }
        if (t & 2) { uint4 u = v0; v0 = v2; v2 = u; u = v1; v1 = v3; v3 = u; }
        unsigned char* dsA = prm.s->xT + oA;
        __stcg((uint4*)dsA, v0); __stcg((uint4*)(dsA + 65536), v1); __stcg((uint4*)(dsA + 131072), v2); __stcg((uint4*)(dsA + 196608), v3);
      } else if (kb == pB) {
        __stcg((uint4*)(prm.s->xT + oB), ldsm4t(raB));
        bar_arrive(8, 288);
      }
    }
    wg_wait<0>();
    if (lane < 2) mbar_arrive_cl(sb + B_EMPTY, lane);
    if (w == 0) STAMPM(169 + 10 * wg);
    reg_fence<120>(acc);
    STAMPW(8 + warp);
    uint32_t ph0[20], ph1[20];
    float pq[40];
    {
      float pk[40];
      const uint64_t dphi = mkdesc(sb + OFF_PHI, 128, 1280, 0);
      const uint32_t rg = (8 * wg + 2 * w) * 128;
      mbar_wait(sb + B_EMPTY + 16, 0);
      {
        uint32_t va[20];
#pragma unroll
        for (int j = 0; j < 10; j++) {
          const int bv = j < 8 ? 16 + j : 20 + j;
          va[2 * j] = pack(acc[4 * bv], acc[4 * bv + 1]); va[2 * j + 1] = pack(acc[4 * bv + 2], acc[4 * bv + 3]);
        }
        const uint32_t v0 = sb + OFF_VB + rg + (lane & 15) * 16;
        const uint32_t hi = lane >> 4;
        stsm4(v0 + (0 + hi) * 2048, va[0], va[1], va[2], va[3]);
        stsm4(v0 + (3 + hi) * 2048, va[4], va[5], va[6], va[7]);
        stsm4(v0 + (5 + hi) * 2048, va[8], va[9], va[10], va[11]);
        stsm4(v0 + (7 + 2 * hi) * 2048, va[12], va[13], va[14], va[15]);
        stsm4(v0 + (10 + hi) * 2048, va[16], va[17], va[18], va[19]);
        sts128(v0 + (2 + 6 * hi) * 2048, 0x3F803F80u, 0x3F803F80u, 0x3F803F80u, 0x3F803F80u);
      }
      uint32_t fq[20];
#pragma unroll
      for (int j = 0; j < 10; j++) {
        const int bq = j < 8 ? j : 16 + j;
        fq[2 * j] = pack(acc[4 * bq], acc[4 * bq + 1]); fq[2 * j + 1] = pack(acc[4 * bq + 2], acc[4 * bq + 3]);
      }
      uint32_t fa[20];
#pragma unroll
      for (int j = 0; j < 10; j++) {
        const int bk = j < 8 ? 8 + j : 18 + j;
        fa[2 * j] = pack(acc[4 * bk], acc[4 * bk + 1]); fa[2 * j + 1] = pack(acc[4 * bk + 2], acc[4 * bk + 3]);
      }
      reg_fence<20>(fa); reg_fence<20>(fq);
      wg_fence();
#pragma unroll
      for (int s = 0; s < 5; s++) wgmma_rs<80, 1>(pk, fa[4 * s], fa[4 * s + 1], fa[4 * s + 2], fa[4 * s + 3], dphi + 16 * s, s > 0);
      wg_commit();
#pragma unroll
      for (int s = 0; s < 5; s++) wgmma_rs<80, 1>(pq, fq[4 * s], fq[4 * s + 1], fq[4 * s + 2], fq[4 * s + 3], dphi + 16 * s, s > 0);
      wg_commit();
      wg_wait<1>();
      reg_fence<40>(pk);
      if (warp == 0) STAMPW(66);
      softmax2(pk, ph0, ph1);
      mbar_wait(sb + B_EMPTY, 1);
      const uint32_t a0 = sb + OFF_PHIK + t * PHIK_HS + rg + g * 16;
#pragma unroll
      for (int c = 0; c < 5; c++) {
        sts128(a0 + c * 2048, ph0[4 * c], ph0[4 * c + 1], ph0[4 * c + 2], ph0[4 * c + 3]);
        sts128(a0 + c * 2048 + 128, ph1[4 * c], ph1[4 * c + 1], ph1[4 * c + 2], ph1[4 * c + 3]);
      }
    }
    fence_async();
    bar_sync(1, 256);
    STAMPW(16 + warp);
    const unsigned ep1 = (ld_rlx(cnt + C_DONE * 32) >> 7) + 1;
    {
      float kv[32];
      wg_fence();
#pragma unroll
      for (int hh = 0; hh < 2; hh++) {
        const uint64_t da = mkdesc(sb + OFF_PHIK + (2 * wg + hh) * PHIK_HS, 128, 2048, 0);
        const uint64_t db = mkdesc(sb + OFF_VB + (6 * wg + 2 * hh) * 2048, 128, 2048, 0);
#pragma unroll
        for (int s = 0; s < 8; s++) wgmma_ss<32, 1, 1>(kv + 16 * hh, da + 16 * s, db + 16 * s, s > 0);
      }
      wg_commit();
      mbar_wait(sb + B_Z, 0);
      wg_wait<0>();
      reg_fence<32>(kv);
      reg_fence<40>(pq);
      if (warp == 0) STAMPW(67);
      if (w < 3) {
        float v[2][12];
#pragma unroll
        for (int r = 0; r < 2; r++) {
          v[r][0] = kv[2 * r]; v[r][1] = kv[2 * r + 1]; v[r][2] = kv[4 + 2 * r]; v[r][3] = kv[5 + 2 * r];
          v[r][4] = t < 2 ? kv[12 + 2 * r] : kv[8 + 2 * r]; v[r][5] = t < 2 ? kv[13 + 2 * r] : 0.f;
          v[r][6] = kv[24 + 2 * r]; v[r][7] = kv[25 + 2 * r]; v[r][8] = kv[28 + 2 * r]; v[r][9] = kv[29 + 2 * r];
          v[r][10] = t < 2 ? kv[16 + 2 * r] : kv[20 + 2 * r]; v[r][11] = t < 2 ? 0.f : kv[21 + 2 * r];
        }
        const uint32_t xa = sb + OFF_KX + w * 3072 + lane * 16;
        if (wg != rank) {
          const uint32_t ra = mapa(xa, wg), rb = mapa(sb + B_KX, wg);
#pragma unroll
          for (int r = 0; r < 2; r++)
            if (r == 0 || w < 2)
#pragma unroll
              for (int i = 0; i < 3; i++) st_async4(ra + r * 1536 + i * 512, v[r][4 * i], v[r][4 * i + 1], v[r][4 * i + 2], v[r][4 * i + 3], rb);
        } else {
          float* b0 = prm.s->kv + (cg * 2 + rank) * 2560 + w * 1024 + lane * 4;
          mbar_wait(sb + B_KX, 0);
          float4 u[2][3];
#pragma unroll
          for (int r = 0; r < 2; r++)
            if (r == 0 || w < 2)
#pragma unroll
              for (int i = 0; i < 3; i++) u[r][i] = lds128f(xa + r * 1536 + i * 512);
#pragma unroll
          for (int r = 0; r < 2; r++)
            if (r == 0 || w < 2) {
              float* b = b0 + r * 512;
              red4(b, v[r][0] + u[r][0].x, v[r][1] + u[r][0].y, v[r][2] + u[r][0].z);
              red4(b + 128, v[r][3] + u[r][0].w, v[r][4] + u[r][1].x, v[r][5] + u[r][1].y);
              red4(b + 256, v[r][6] + u[r][1].z, v[r][7] + u[r][1].w, v[r][8] + u[r][2].x);
              red4(b + 384, v[r][9] + u[r][2].y, v[r][10] + u[r][2].z, v[r][11] + u[r][2].w);
            }
          bar_arrive(2, 128);
          if (w == 0) STAMPW(98);
        }
      }
      __syncwarp();
      if (lane < 4) mbar_arrive_cl(sb + B_EMPTYO + 8 * (lane >> 1), lane & 1);
    }
    softmax2(pq, ph0, ph1);
    reg_fence<20>(ph0); reg_fence<20>(ph1);
    STAMPW(24 + warp);
    {
      const int h = lane >> 3, fb = (lane >> 2) & 1;
      const float* src = prm.s->kv + (cg * 2 + (h >> 1)) * 2560 + (warp >> 2) * 512 + (h & 1) * 256 + ((2 * (warp & 3) + fb) * 4 + t) * 4;
      const int j0 = t + 2 * (h & 1), j2 = (h & 1) ? (t == 0 ? 10 : t - 2) : 8 + t;
      const bool has2 = t != ((h & 1) ? 1 : 3);
      const uint32_t dst = sb + OFF_KVB + warp * 128 + (2 * h + fb) * 16 + 4 * h;
      float4 f[3][2];
      if (lane == 0) poll(cnt + (C_KV + cg) * 32, 16 * ep1);
      __syncwarp();
      if (warp == 0) STAMPW(50);
#pragma unroll
      for (int i = 0; i < 3; i++)
        if (i < 2 || warp < 4) { f[i][0] = ld_rlx4(src + i * 1024); f[i][1] = ld_rlx4(src + i * 1024 + 128); }
#pragma unroll
      for (int i = 0; i < 3; i++)
        if (i < 2 || warp < 4) {
          sts32(dst + i * 1024 + j0 * KVB_S, pack(f[i][0].x, f[i][0].y));
          sts32(dst + i * 1024 + (j0 + 4) * KVB_S, pack(f[i][0].z, f[i][1].x));
          if (has2) sts32(dst + i * 1024 + j2 * KVB_S, pack(f[i][1].y, f[i][1].z));
        }
    }
    fence_async();
    bar_sync(1, 256);
    {
      float p[44];
      if (warp == 0) STAMPW(68);
      const uint64_t db = mkdesc(sb + OFF_KVB, 128, KVB_S, 0);
      wg_fence();
#pragma unroll
      for (int s = 0; s < 10; s++) wgmma_rs<88, 1>(p, ph0[2 * s], ph1[2 * s], ph0[2 * s + 1], ph1[2 * s + 1], db + 16 * s, s > 0);
      wg_commit();
      wg_wait<0>();
      reg_fence<44>(p);
      if (warp == 0) STAMPW(69);
      if (lane < 4) mbar_arrive_cl(sb + B_EMPTYO + 16 + 8 * (lane >> 1), lane & 1);
      const float r0 = rcp(p[40] + 1e-6f), r1 = rcp(p[42] + 1e-6f);
      uint32_t* o = (uint32_t*)(prm.s->o + (rt * 8 + cg) * 20480 + (8 * wg + 2 * w) * 128) + lane;
#pragma unroll
      for (int j = 0; j < 10; j++) {
        __stcg(o + j * 512, pack(p[4 * j] * r0, p[4 * j + 1] * r0));
        __stcg(o + j * 512 + 32, pack(p[4 * j + 2] * r1, p[4 * j + 3] * r1));
      }
      __syncwarp();
      if (lane == 0) red_rel(cnt + (C_O + rt) * 32 + cg);
    }
    if (warp == 0) STAMPW(51);
    float p[40];
#pragma unroll
    for (int i = 0; i < 40; i++) p[i] = 0.f;
    reg_fence<40>(p);
    mbar_wait(sb + B_WO, 0);
#pragma unroll 1
    for (int i = 0; i < 8; i++) {
      const int st = i & 3;
      const uint32_t oa = sb + (st < 2 ? OFF_S : OFF_PHI) + (st & 1) * 20480 + wg * 1024;
      const uint32_t wa = OFF_WO + (((i + 3) & 7) - 3) * 10240;
      const uint32_t ta = OFF_WOT + (i >> 2) * 10240 + (i & 3) * 32;
      const uint64_t da = mkdesc(oa, 2048, 128, 0);
      const uint64_t db = mkdesc(sb + wa, ta - wa, 1024, 1);
      mbar_wait(sb + B_FULLO + 8 * st, i >> 2);
      if (warp == 0) STAMPW(52 + i);
      wg_fence();
#pragma unroll
      for (int ks = 0; ks < 5; ks++) wgmma_ss<80, 0, 1>(p, da + 256 * ks, db + 128 * ks, 1);
      wg_commit();
      wg_wait<0>();
      if (i < 6 && lane < 2) mbar_arrive_cl(sb + B_EMPTYO + 8 * st, lane);
    }
    reg_fence<40>(p);
    if (warp == 0) STAMPW(60);
    mbar_wait(sb + B_Y, 0);
    mbar_wait(sb + B_EMPTYO + 8, 0);
    if (warp == 0) STAMPW(61);
    {
      const int r0 = 64 * wg + 16 * w + g;
      const float l0 = __uint_as_float(lds32(sb + OFF_G + r0 * 4)), l1 = __uint_as_float(lds32(sb + OFF_G + r0 * 4 + 32));
      const float g0 = rcp(1.f + ex2(-1.4426950408889634f * l0)), g1 = rcp(1.f + ex2(-1.4426950408889634f * l1));
      const uint32_t ya = sb + OFF_S + ((lane >> 4) * 8 + (lane & 7)) * 256 + (((8 * wg + 2 * w + ((lane >> 3) & 1)) ^ (lane & 7)) * 16);
      const uint32_t ob = sb + OFF_S + 20480 + warp * 2560;
      const uint32_t oa = ob + (lane & 15) * 160 + (lane >> 4) * 16;
#pragma unroll
      for (int j = 0; j < 5; j++) {
        const uint4 y = ldsm4t(ya + j * 4096);
        const float* a = p + 8 * j;
        uint32_t o0 = pack(fmaf(g0, a[0] - blo(y.x), blo(y.x)), fmaf(g0, a[1] - bhi(y.x), bhi(y.x)));
        uint32_t o1 = pack(fmaf(g1, a[2] - blo(y.y), blo(y.y)), fmaf(g1, a[3] - bhi(y.y), bhi(y.y)));
        uint32_t o2 = pack(fmaf(g0, a[4] - blo(y.z), blo(y.z)), fmaf(g0, a[5] - bhi(y.z), bhi(y.z)));
        uint32_t o3 = pack(fmaf(g1, a[6] - blo(y.w), blo(y.w)), fmaf(g1, a[7] - bhi(y.w), bhi(y.w)));
        stsm4(oa + j * 32, o0, o1, o2, o3);
      }
      fence_async();
      __syncwarp();
      if (lane == 0) {
        tma_st2d(&tmOut, ob, 80 * ct3, 128 * rt3 + 16 * warp);
        asm volatile("cp.async.bulk.commit_group;\ncp.async.bulk.wait_group.read 0;" ::: "memory");
      }
    }
    STAMPW(32 + warp);
    }
  } else if (warp < 12) {
    const int w = warp & 3;
    {
      const uint4* xr = prm.x + (128 * rt + 16 * cg + (th >> 4)) * 80 + (th & 15);
      uint4 xv[2][5], gv[5];
#pragma unroll
      for (int j = 0; j < 5; j++) { xv[0][j] = __ldcg(xr + j * 16); xv[1][j] = __ldcg(xr + 640 + j * 16); gv[j] = __ldg(prm.gw + (th & 15) + j * 16); }
      float a[2] = {0.f, 0.f};
#pragma unroll
      for (int j = 0; j < 5; j++)
#pragma unroll
        for (int r = 0; r < 2; r++) {
          a[r] = fmaf(blo(xv[r][j].x), blo(gv[j].x), a[r]); a[r] = fmaf(bhi(xv[r][j].x), bhi(gv[j].x), a[r]);
          a[r] = fmaf(blo(xv[r][j].y), blo(gv[j].y), a[r]); a[r] = fmaf(bhi(xv[r][j].y), bhi(gv[j].y), a[r]);
          a[r] = fmaf(blo(xv[r][j].z), blo(gv[j].z), a[r]); a[r] = fmaf(bhi(xv[r][j].z), bhi(gv[j].z), a[r]);
          a[r] = fmaf(blo(xv[r][j].w), blo(gv[j].w), a[r]); a[r] = fmaf(bhi(xv[r][j].w), bhi(gv[j].w), a[r]);
        }
      float v = (th & 1 ? a[1] : a[0]) + __shfl_xor_sync(0xffffffffu, th & 1 ? a[0] : a[1], 1);
      v += __shfl_xor_sync(0xffffffffu, v, 2); v += __shfl_xor_sync(0xffffffffu, v, 4); v += __shfl_xor_sync(0xffffffffu, v, 8);
      if ((th & 14) == 0) __stcg(prm.s->gate + 128 * rt + 16 * cg + (th >> 4) + 8 * (th & 1), v);
      __syncwarp();
      if (lane == 0) mbar_arrive(sb + B_Z);
      if (w == 0) STAMPW(99);
    }
    bar_sync(15, 192);
    if (w == 0) STAMPW(92);
    uint32_t ka = sb + OFF_KT + 4 * 4160 + 2 * (2064 - 16 * w - 2 * g + 4 * t);
    uint32_t fa[4][8];
    conv_raw<0>(ka, fa[0]); conv_raw<1>(ka, fa[1]);
    conv_perm(fa[0]);
#pragma unroll 1
    for (int j = 0; j < 5; j++) {
      float acc[64];
#pragma unroll
      for (int i = 0; i < 64; i++) acc[i] = 0.f;
      reg_fence<64>(acc);
      mbar_wait(sb + B_FULLU + 8 * (j & 1), (j >> 1) & 1);
      if (w == 0) STAMPW(70 + j);
      ConvLoop<0>::run(acc, ka, mkdesc(sb + OFF_U + (j & 1) * 4480, 2240, 128, 0), fa);
      ka -= 4160;
      wg_wait<0>();
      reg_fence<64>(acc);
      if (w == 0) STAMPW(75 + j);
      bar_sync(6, 192);
      const uint32_t pa = sb + OFF_P + w * 4096 + ((lane >> 3) & 1) * 2048 + ((lane >> 4) * 8 + (lane & 7)) * 16;
#pragma unroll
      for (int i = 0; i < 8; i++) {
        const float* a = acc + 8 * i;
        stsm4t(pa + i * 256, pack(a[0], a[1]), pack(a[2], a[3]), pack(a[4], a[5]), pack(a[6], a[7]));
      }
      bar_arrive(5, 192);
    }
  } else {
    asm volatile("setmaxnreg.dec.sync.aligned.u32 48;");
    if (warp < 14) bar_arrive(3, 128);
    if (warp == 12) {
      if (lane == 0) {
        asm volatile("prefetch.tensormap [%0];" ::"l"(&tmWo) : "memory");
        asm volatile("prefetch.tensormap [%0];" ::"l"(&tmOut) : "memory");
        asm volatile("cp.async.bulk.prefetch.L2.global [%0], 13440;" ::"l"((const char*)prm.w + 192 * 3840 + cta * 13440) : "memory");
        for (int i = 0; i < 16; i++)
          asm volatile("cp.async.bulk.prefetch.L2.global [%0], 896;" ::"l"((const char*)prm.x + (16 * cta + i) * 1280 + 384) : "memory");
        asm volatile("cp.async.bulk.prefetch.L2.global [%0], 6400;" ::"l"((const char*)prm.wo + cta * 6400) : "memory");
        const int kv_ = 8 + (cg >> 2), p0 = cg < 3 ? 4 : 5;
#pragma unroll 1
        for (int p = 0; p < 7; p++) {
          const int s = p % 3;
          const uint32_t st = sb + OFF_S + ((3 - s) % 3) * STG, bar = sb + B_FULL + 8 * s;
          int kb = p + 6 - p0;
          if (cg >= 3 && kb >= cg) kb++;
          if (kb >= kv_) kb++;
          if (p + 4 == p0) kb = kv_;
          if (p + 5 == p0) kb = cg;
          mbar_wait(sb + B_EMPTY + 8 * s, (p / 3) & 1);
          STAMP(180 + p);
          mbar_expect(bar, STG_TX);
          tma2d(st, &tmX, 64 * kb, 128 * rt, bar);
          tma3d_mc(st + 16384 + rank * 16384, &tmW, 80 * cg, 64 * kb + 32 * rank, 0, bar);
          tma3d_mc(st + 16384 + rank * 16384 + 12288, &tmWt, 80 * cg + 64, 64 * kb + 32 * rank, 0, bar);
          STAMP(190 + p);
        }
        const uint32_t wb = sb + B_WO;
        mbar_wait(sb + B_EMPTY + 8, 0);
        mbar_arrive(sb + B_T);
        mbar_expect(wb, 20480);
        for (int u = 3; u < 5; u++) tma5d(sb + OFF_WO + u * 10240, &tmWo, 80 * ct3, 0, 0, 0, u, wb);
        mbar_wait(sb + B_EMPTY + 16, 0);
        mbar_expect(wb, 30720);
        for (int u = 0; u < 3; u++) tma5d(sb + OFF_WO + u * 10240, &tmWo, 80 * ct3, 0, 0, 0, u, wb);
      }
      __syncwarp();
      const unsigned ep1 = (ld_rlx(cnt + C_DONE * 32) >> 7) + 1;
      bar_sync(2, 128);
      STAMPW(120);
      if (lane == 0) red_rel(cnt + (C_KV + cg) * 32);
      STAMPW(121);
      if (lane == 0) {
        const uint32_t wb = sb + B_WO;
        mbar_wait(sb + B_EMPTYO, 0);
        mbar_expect(wb, 30720);
        for (int u = 5; u < 8; u++) tma5d(sb + OFF_WO + (u - 8) * 10240, &tmWo, 80 * ct3, 0, 0, 0, u, wb);
      }
      __syncwarp();
      {
        unsigned ready = 0;
        int next = 0, n = 0;
        while (next < 8) {
          bool ok = false;
          if (lane < 8 && !((ready >> lane) & 1)) ok = (int)(ld_acq(cnt + (C_O + rt3) * 32 + lane) - 8 * ep1) >= 0;
          ready |= __ballot_sync(0xffffffffu, ok);
          while (next < 8 && ((ready >> next) & 1)) {
            if (lane == next) {
              const int st = next & 3;
              const uint32_t oa = sb + (st < 2 ? OFF_S : OFF_PHI) + (st & 1) * 20480;
              mbar_wait(sb + B_EMPTYO + 8 * st, next >> 2);
              fence_async_g();
              mbar_expect(sb + B_FULLO + 8 * st, 20480);
              bulk_ld_mc(oa + rank * 10240, prm.s->o + (rt3 * 8 + next) * 20480 + rank * 10240, 10240, sb + B_FULLO + 8 * st);
            }
            __syncwarp();
            next++;
          }
          if (++n > SPIN_MAX) __trap();
        }
      }
      if (lane == 0) {
        poll(cnt + (C_Y + ct3) * 32, 32 * ep1);
        mbar_wait(sb + B_EMPTYO, 0);
        fence_async_g();
        mbar_expect(sb + B_Y, 20480 + 512);
        bulk_ld(sb + OFF_S, prm.s->y + (rt3 * 640 + 80 * ct3) * 256, 20480, sb + B_Y);
        bulk_ld(sb + OFF_G, prm.s->gate + rt3 * 128, 512, sb + B_Y);
        red_rlx(cnt + C_DONE * 32);
      }
    } else if (warp == 13) {
      const unsigned ep1 = (ld_rlx(cnt + C_DONE * 32) >> 7) + 1;
      {
        float4* z = (float4*)prm.s->kv + cg * 1280 + rt * 80;
        z[lane] = make_float4(0.f, 0.f, 0.f, 0.f); z[lane + 32] = make_float4(0.f, 0.f, 0.f, 0.f);
        if (lane < 16) z[lane + 64] = make_float4(0.f, 0.f, 0.f, 0.f);
      }
#pragma unroll
      for (int i = 0; i < 2; i++)
        if ((lane & 15) < 12) sts128(sb + OFF_U + (2 * i + (lane >> 4)) * 2240 + 2048 + (lane & 15) * 16, 0, 0, 0, 0);
      fence_async();
      bar_sync(8, 288);
      STAMPW(93);
      if (lane == 0) {
        red_rel(cnt + C_X * 32);
        STAMP(94);
      }
      bar_sync(7, 96);
      if (lane == 0) {
        poll(cnt + C_X * 32, 128 * ep1);
        mbar_arrive(sb + B_Z);
        fence_async_g();
        for (int j = 0; j < 2; j++) {
          const uint32_t bar = sb + B_FULLU + 8 * j, ub = sb + OFF_U + j * 4480;
          const unsigned char* src = prm.s->xT + (5 * cta + j) * 4096;
          mbar_expect(bar, 4096);
          bulk_ld(ub, src, 2048, bar);
          bulk_ld(ub + 2240, src + 2048, 2048, bar);
        }
      }
      __syncwarp();
      STAMPW(95);
      mbar_wait(sb + B_T, 0);
      {
        const int c = lane & 1, rr = lane >> 1;
        const uint16_t* src = prm.wo + (20 * ((rr >> 1) & 3) + 2 * (rr >> 3) + (rr & 1)) * 640 + 80 * ct3 + 64 + 8 * c;
#pragma unroll
        for (int q = 0; q < 4; q++) {
          const uint32_t d = sb + OFF_WOT + rr * 128 + (((2 * q + c) ^ (rr & 7)) * 16);
#pragma unroll
          for (int i = 0; i < 10; i++)
            asm volatile("cp.async.cg.shared.global [%0], [%1], 16;" ::"r"(d + (i / 5) * 10240 + (i % 5) * 2048), "l"(src + (80 * (q + 4 * (i / 5)) + 4 * (i % 5)) * 640) : "memory");
        }
      }
      asm volatile("cp.async.wait_all;" ::: "memory");
      fence_async();
      __syncwarp();
      if (lane == 0) mbar_arrive(sb + B_WO);
      STAMPW(97);
    } else {
      const int t64 = tid & 63;
      bar_sync(3, 128);
#pragma unroll 1
      for (int i = 0; i < 5; i++) {
        const int j = i < 2 ? 1 - i : i;
        if (i) bar_sync(10 + i, 192);
        const uint32_t kt = sb + OFF_KT + (4 - j) * 4160, kv = sb + (j < 4 ? OFF_U + j * 2240 : OFF_P + 4160);
        const uint32_t dst = kt + 2 * (2064 - 16 * t64 - 16);
        expand16<3>(kv, 512 + 2 * t64, dst - 2048);
        if (t64 >= 32) expand16<2>(kv, 384 + 4 * (t64 - 32), dst);
        else if (t64 >= 16) expand16<1>(kv, 256 + 8 * (t64 - 16), dst);
        else expand16<0>(kv, 16 * t64, dst);
        if (t64 == 63) {
          sts128(kt + 2 * 2064, lds16(kv), 0, 0, 0);
          sts128(kt + 2 * 2064 + 16, 0, 0, 0, 0);
        }
        if (warp == 14) STAMPW(85 + i);
      }
      bar_arrive(15, 192);
      bar_arrive(6, 192);
#pragma unroll 4
      for (int i = 0; i < 28; i++) sts128(sb + OFF_KVB + (i * 64 + t64) * 16, 0, 0, 0, 0);
      fence_async();
      bar_arrive(7, 96);
      if (warp == 14) STAMPW(96);
#pragma unroll 1
      for (int j = 0; j < 5; j++) {
        const int ch = 5 * cta + j;
        bar_sync(5, 192);
        if (j < 3 && t64 == 0) {
          const uint32_t bar = sb + B_FULLU + 8 * (j & 1), ub = sb + OFF_U + (j & 1) * 4480;
          const unsigned char* src = prm.s->xT + (ch + 2) * 4096;
          fence_async_g();
          mbar_expect(bar, 4096);
          bulk_ld(ub, src, 2048, bar);
          bulk_ld(ub + 2240, src + 2048, 2048, bar);
        }
#pragma unroll 1
        for (int it = 0; it < 2; it++) {
          const int th = t64 + 64 * it;
          uint4 e[4], o[4];
#pragma unroll
          for (int ww = 0; ww < 4; ww++) {
            const uint32_t pa = sb + OFF_P + ww * 4096 + (127 - th + ww) * 16, za = sb + OFF_U + 2048;
            e[ww] = lds128(th >= ww ? pa : za); o[ww] = lds128(th >= ww ? pa + 2048 : za);
          }
#define SUM4(f, a, c) ((f(a[0].c) + f(a[1].c)) + (f(a[2].c) + f(a[3].c)))
          unsigned char* yb = prm.s->y + ((th >> 3) * 640 + ch) * 256;
          const int c0 = 2 * (th & 7), sw = ch & 7;
          __stcg((uint4*)(yb + ((c0 ^ sw) * 16)), make_uint4(pack(SUM4(blo, e, x), SUM4(blo, o, x)), pack(SUM4(bhi, e, x), SUM4(bhi, o, x)),
                                                             pack(SUM4(blo, e, y), SUM4(blo, o, y)), pack(SUM4(bhi, e, y), SUM4(bhi, o, y))));
          __stcg((uint4*)(yb + (((c0 + 1) ^ sw) * 16)), make_uint4(pack(SUM4(blo, e, z), SUM4(blo, o, z)), pack(SUM4(bhi, e, z), SUM4(bhi, o, z)),
                                                                   pack(SUM4(blo, e, w), SUM4(blo, o, w)), pack(SUM4(bhi, e, w), SUM4(bhi, o, w))));
        }
        if (j < 4) bar_arrive(6, 192);
        if (warp == 14) STAMPW(80 + j);
      }
      __syncwarp();
      if (lane == 0) red_rel(cnt + (C_Y + (cta >> 4)) * 32 );
    }
  }
}

typedef CUresult (*EncFn)(CUtensorMap*, CUtensorMapDataType, cuuint32_t, void*, const cuuint64_t*, const cuuint64_t*, const cuuint32_t*,
                          const cuuint32_t*, CUtensorMapInterleave, CUtensorMapSwizzle, CUtensorMapL2promotion, CUtensorMapFloatOOBfill);
int enc(EncFn fn, CUtensorMap* m, void* p, int rank, const cuuint64_t* gd, const cuuint64_t* gs, const cuuint32_t* bd, CUtensorMapSwizzle sw) {
  const cuuint32_t es[5] = {1, 1, 1, 1, 1};
  return (int)fn(m, CU_TENSOR_MAP_DATA_TYPE_BFLOAT16, rank, p, gd, gs, bd, es, CU_TENSOR_MAP_INTERLEAVE_NONE, sw,
                 CU_TENSOR_MAP_L2_PROMOTION_L2_128B, CU_TENSOR_MAP_FLOAT_OOB_FILL_NONE);
}
int g_enc_err = 0;
}

extern "C" void kernel_launch(void* const* d_in, const int* in_sizes, int n_in, void* d_out, int out_size) {
  static EncFn fn = nullptr;
  static Scratch* scr = nullptr;
  if (!fn) {
    void* p = nullptr;
    cudaDriverEntryPointQueryResult qr;
    cudaGetDriverEntryPoint("cuTensorMapEncodeTiled", &p, cudaEnableDefault, &qr);
    fn = (EncFn)p;
    cudaGetSymbolAddress((void**)&scr, g_s);
    cudaFuncSetAttribute(fused_kernel, cudaFuncAttributeMaxDynamicSharedMemorySize, SMEM_BYTES + 512);
  }
  CUtensorMap mX, mW, mWt, mWo, mOut;
  int e = 0;
  { cuuint64_t gd[2] = {640, 2048}, gs[1] = {1280}; cuuint32_t bd[2] = {64, 128}; e |= enc(fn, &mX, d_in[0], 2, gd, gs, bd, CU_TENSOR_MAP_SWIZZLE_128B); }
  { cuuint64_t gd[3] = {640, 640, 3}, gs[2] = {3840, 1280}; cuuint32_t bd[3] = {64, 32, 3}; e |= enc(fn, &mW, d_in[1], 3, gd, gs, bd, CU_TENSOR_MAP_SWIZZLE_128B) << 4; }
  { cuuint64_t gd[3] = {640, 640, 3}, gs[2] = {3840, 1280}; cuuint32_t bd[3] = {16, 32, 3}; e |= enc(fn, &mWt, d_in[1], 3, gd, gs, bd, CU_TENSOR_MAP_SWIZZLE_32B) << 8; }
  { cuuint64_t gd[5] = {640, 2, 4, 10, 8}, gs[4] = {1280, 25600, 2560, 102400}; cuuint32_t bd[5] = {64, 2, 4, 10, 1}; e |= enc(fn, &mWo, d_in[3], 5, gd, gs, bd, CU_TENSOR_MAP_SWIZZLE_128B) << 12; }
  { cuuint64_t gd[2] = {640, 2048}, gs[1] = {1280}; cuuint32_t bd[2] = {80, 16}; e |= enc(fn, &mOut, d_out, 2, gd, gs, bd, CU_TENSOR_MAP_SWIZZLE_NONE) << 20; }
  g_enc_err = e;
  if (e) return;
  Params prm;
  prm.s = scr; prm.wo = (const uint16_t*)d_in[3]; prm.lar = (const uint16_t*)d_in[5]; prm.aim = (const uint16_t*)d_in[6];
  prm.cre = (const uint16_t*)d_in[7]; prm.cim = (const uint16_t*)d_in[8]; prm.ldt = (const uint16_t*)d_in[9]; prm.dsk = (const uint16_t*)d_in[10];
  prm.wphi = (const uint32_t*)d_in[2]; prm.gw = (const uint4*)d_in[11]; prm.x = (const uint4*)d_in[0]; prm.w = (const uint4*)d_in[1];
  fused_kernel<<<128, 512, SMEM_BYTES + 512, cudaStreamPerThread>>>(prm, mX, mW, mWt, mWo, mOut);
}
```

```cpp
#include <cuda_runtime.h>
#include <cuda_bf16.h>
#include <cuda.h>
#include <stdint.h>

template<int N, int TA, int TB> __device__ __forceinline__ void wgmma_ss(float* d, uint64_t da, uint64_t db, int sd);
template<int N, int TB> __device__ __forceinline__ void wgmma_rs(float* d, uint32_t a0, uint32_t a1, uint32_t a2, uint32_t a3, uint64_t db, int sd);
template<> __device__ __forceinline__ void wgmma_ss<192,0,1>(float* d, uint64_t da, uint64_t db, int sd) {
  asm volatile("{\n.reg .pred p;\nsetp.ne.b32 p, %98, 0;\n"
  "wgmma.mma_async.sync.aligned.m64n192k16.f32.bf16.bf16 {%0,%1,%2,%3,%4,%5,%6,%7,%8,%9,%10,%11,%12,%13,%14,%15,%16,%17,%18,%19,%20,%21,%22,%23,%24,%25,%26,%27,%28,%29,%30,%31,%32,%33,%34,%35,%36,%37,%38,%39,%40,%41,%42,%43,%44,%45,%46,%47,%48,%49,%50,%51,%52,%53,%54,%55,%56,%57,%58,%59,%60,%61,%62,%63,%64,%65,%66,%67,%68,%69,%70,%71,%72,%73,%74,%75,%76,%77,%78,%79,%80,%81,%82,%83,%84,%85,%86,%87,%88,%89,%90,%91,%92,%93,%94,%95}, %96, %97, p, 1, 1, 0, 1;\n}\n"
  : "+f"(d[0]),"+f"(d[1]),"+f"(d[2]),"+f"(d[3]),"+f"(d[4]),"+f"(d[5]),"+f"(d[6]),"+f"(d[7]),"+f"(d[8]),"+f"(d[9]),"+f"(d[10]),"+f"(d[11]),"+f"(d[12]),"+f"(d[13]),"+f"(d[14]),"+f"(d[15]),"+f"(d[16]),"+f"(d[17]),"+f"(d[18]),"+f"(d[19]),"+f"(d[20]),"+f"(d[21]),"+f"(d[22]),"+f"(d[23]),"+f"(d[24]),"+f"(d[25]),"+f"(d[26]),"+f"(d[27]),"+f"(d[28]),"+f"(d[29]),"+f"(d[30]),"+f"(d[31]),"+f"(d[32]),"+f"(d[33]),"+f"(d[34]),"+f"(d[35]),"+f"(d[36]),"+f"(d[37]),"+f"(d[38]),"+f"(d[39]),"+f"(d[40]),"+f"(d[41]),"+f"(d[42]),"+f"(d[43]),"+f"(d[44]),"+f"(d[45]),"+f"(d[46]),"+f"(d[47]),"+f"(d[48]),"+f"(d[49]),"+f"(d[50]),"+f"(d[51]),"+f"(d[52]),"+f"(d[53]),"+f"(d[54]),"+f"(d[55]),"+f"(d[56]),"+f"(d[57]),"+f"(d[58]),"+f"(d[59]),"+f"(d[60]),"+f"(d[61]),"+f"(d[62]),"+f"(d[63]),"+f"(d[64]),"+f"(d[65]),"+f"(d[66]),"+f"(d[67]),"+f"(d[68]),"+f"(d[69]),"+f"(d[70]),"+f"(d[71]),"+f"(d[72]),"+f"(d[73]),"+f"(d[74]),"+f"(d[75]),"+f"(d[76]),"+f"(d[77]),"+f"(d[78]),"+f"(d[79]),"+f"(d[80]),"+f"(d[81]),"+f"(d[82]),"+f"(d[83]),"+f"(d[84]),"+f"(d[85]),"+f"(d[86]),"+f"(d[87]),"+f"(d[88]),"+f"(d[89]),"+f"(d[90]),"+f"(d[91]),"+f"(d[92]),"+f"(d[93]),"+f"(d[94]),"+f"(d[95]) : "l"(da), "l"(db), "r"(sd));
}
template<> __device__ __forceinline__ void wgmma_ss<56,0,1>(float* d, uint64_t da, uint64_t db, int sd) {
  asm volatile("{\n.reg .pred p;\nsetp.ne.b32 p, %30, 0;\n"
  "wgmma.mma_async.sync.aligned.m64n56k16.f32.bf16.bf16 {%0,%1,%2,%3,%4,%5,%6,%7,%8,%9,%10,%11,%12,%13,%14,%15,%16,%17,%18,%19,%20,%21,%22,%23,%24,%25,%26,%27}, %28, %29, p, 1, 1, 0, 1;\n}\n"
  : "+f"(d[0]),"+f"(d[1]),"+f"(d[2]),"+f"(d[3]),"+f"(d[4]),"+f"(d[5]),"+f"(d[6]),"+f"(d[7]),"+f"(d[8]),"+f"(d[9]),"+f"(d[10]),"+f"(d[11]),"+f"(d[12]),"+f"(d[13]),"+f"(d[14]),"+f"(d[15]),"+f"(d[16]),"+f"(d[17]),"+f"(d[18]),"+f"(d[19]),"+f"(d[20]),"+f"(d[21]),"+f"(d[22]),"+f"(d[23]),"+f"(d[24]),"+f"(d[25]),"+f"(d[26]),"+f"(d[27]) : "l"(da), "l"(db), "r"(sd));
}
template<> __device__ __forceinline__ void wgmma_ss<48,1,1>(float* d, uint64_t da, uint64_t db, int sd) {
  asm volatile("{\n.reg .pred p;\nsetp.ne.b32 p, %26, 0;\n"
  "wgmma.mma_async.sync.aligned.m64n48k16.f32.bf16.bf16 {%0,%1,%2,%3,%4,%5,%6,%7,%8,%9,%10,%11,%12,%13,%14,%15,%16,%17,%18,%19,%20,%21,%22,%23}, %24, %25, p, 1, 1, 1, 1;\n}\n"
  : "+f"(d[0]),"+f"(d[1]),"+f"(d[2]),"+f"(d[3]),"+f"(d[4]),"+f"(d[5]),"+f"(d[6]),"+f"(d[7]),"+f"(d[8]),"+f"(d[9]),"+f"(d[10]),"+f"(d[11]),"+f"(d[12]),"+f"(d[13]),"+f"(d[14]),"+f"(d[15]),"+f"(d[16]),"+f"(d[17]),"+f"(d[18]),"+f"(d[19]),"+f"(d[20]),"+f"(d[21]),"+f"(d[22]),"+f"(d[23]) : "l"(da), "l"(db), "r"(sd));
}
template<> __device__ __forceinline__ void wgmma_rs<80,1>(float* d, uint32_t a0, uint32_t a1, uint32_t a2, uint32_t a3, uint64_t db, int sd) {
  asm volatile("{\n.reg .pred p;\nsetp.ne.b32 p, %45, 0;\n"
  "wgmma.mma_async.sync.aligned.m64n80k16.f32.bf16.bf16 {%0,%1,%2,%3,%4,%5,%6,%7,%8,%9,%10,%11,%12,%13,%14,%15,%16,%17,%18,%19,%20,%21,%22,%23,%24,%25,%26,%27,%28,%29,%30,%31,%32,%33,%34,%35,%36,%37,%38,%39}, {%40,%41,%42,%43}, %44, p, 1, 1, 1;\n}\n"
  : "+f"(d[0]),"+f"(d[1]),"+f"(d[2]),"+f"(d[3]),"+f"(d[4]),"+f"(d[5]),"+f"(d[6]),"+f"(d[7]),"+f"(d[8]),"+f"(d[9]),"+f"(d[10]),"+f"(d[11]),"+f"(d[12]),"+f"(d[13]),"+f"(d[14]),"+f"(d[15]),"+f"(d[16]),"+f"(d[17]),"+f"(d[18]),"+f"(d[19]),"+f"(d[20]),"+f"(d[21]),"+f"(d[22]),"+f"(d[23]),"+f"(d[24]),"+f"(d[25]),"+f"(d[26]),"+f"(d[27]),"+f"(d[28]),"+f"(d[29]),"+f"(d[30]),"+f"(d[31]),"+f"(d[32]),"+f"(d[33]),"+f"(d[34]),"+f"(d[35]),"+f"(d[36]),"+f"(d[37]),"+f"(d[38]),"+f"(d[39]) : "r"(a0), "r"(a1), "r"(a2), "r"(a3), "l"(db), "r"(sd));
}
template<> __device__ __forceinline__ void wgmma_ss<32,1,1>(float* d, uint64_t da, uint64_t db, int sd) {
  asm volatile("{\n.reg .pred p;\nsetp.ne.b32 p, %18, 0;\n"
  "wgmma.mma_async.sync.aligned.m64n32k16.f32.bf16.bf16 {%0,%1,%2,%3,%4,%5,%6,%7,%8,%9,%10,%11,%12,%13,%14,%15}, %16, %17, p, 1, 1, 1, 1;\n}\n"
  : "+f"(d[0]),"+f"(d[1]),"+f"(d[2]),"+f"(d[3]),"+f"(d[4]),"+f"(d[5]),"+f"(d[6]),"+f"(d[7]),"+f"(d[8]),"+f"(d[9]),"+f"(d[10]),"+f"(d[11]),"+f"(d[12]),"+f"(d[13]),"+f"(d[14]),"+f"(d[15]) : "l"(da), "l"(db), "r"(sd));
}
template<> __device__ __forceinline__ void wgmma_rs<88,1>(float* d, uint32_t a0, uint32_t a1, uint32_t a2, uint32_t a3, uint64_t db, int sd) {
  asm volatile("{\n.reg .pred p;\nsetp.ne.b32 p, %49, 0;\n"
  "wgmma.mma_async.sync.aligned.m64n88k16.f32.bf16.bf16 {%0,%1,%2,%3,%4,%5,%6,%7,%8,%9,%10,%11,%12,%13,%14,%15,%16,%17,%18,%19,%20,%21,%22,%23,%24,%25,%26,%27,%28,%29,%30,%31,%32,%33,%34,%35,%36,%37,%38,%39,%40,%41,%42,%43}, {%44,%45,%46,%47}, %48, p, 1, 1, 1;\n}\n"
  : "+f"(d[0]),"+f"(d[1]),"+f"(d[2]),"+f"(d[3]),"+f"(d[4]),"+f"(d[5]),"+f"(d[6]),"+f"(d[7]),"+f"(d[8]),"+f"(d[9]),"+f"(d[10]),"+f"(d[11]),"+f"(d[12]),"+f"(d[13]),"+f"(d[14]),"+f"(d[15]),"+f"(d[16]),"+f"(d[17]),"+f"(d[18]),"+f"(d[19]),"+f"(d[20]),"+f"(d[21]),"+f"(d[22]),"+f"(d[23]),"+f"(d[24]),"+f"(d[25]),"+f"(d[26]),"+f"(d[27]),"+f"(d[28]),"+f"(d[29]),"+f"(d[30]),"+f"(d[31]),"+f"(d[32]),"+f"(d[33]),"+f"(d[34]),"+f"(d[35]),"+f"(d[36]),"+f"(d[37]),"+f"(d[38]),"+f"(d[39]),"+f"(d[40]),"+f"(d[41]),"+f"(d[42]),"+f"(d[43]) : "r"(a0), "r"(a1), "r"(a2), "r"(a3), "l"(db), "r"(sd));
}
template<> __device__ __forceinline__ void wgmma_ss<80,0,1>(float* d, uint64_t da, uint64_t db, int sd) {
  asm volatile("{\n.reg .pred p;\nsetp.ne.b32 p, %42, 0;\n"
  "wgmma.mma_async.sync.aligned.m64n80k16.f32.bf16.bf16 {%0,%1,%2,%3,%4,%5,%6,%7,%8,%9,%10,%11,%12,%13,%14,%15,%16,%17,%18,%19,%20,%21,%22,%23,%24,%25,%26,%27,%28,%29,%30,%31,%32,%33,%34,%35,%36,%37,%38,%39}, %40, %41, p, 1, 1, 0, 1;\n}\n"
  : "+f"(d[0]),"+f"(d[1]),"+f"(d[2]),"+f"(d[3]),"+f"(d[4]),"+f"(d[5]),"+f"(d[6]),"+f"(d[7]),"+f"(d[8]),"+f"(d[9]),"+f"(d[10]),"+f"(d[11]),"+f"(d[12]),"+f"(d[13]),"+f"(d[14]),"+f"(d[15]),"+f"(d[16]),"+f"(d[17]),"+f"(d[18]),"+f"(d[19]),"+f"(d[20]),"+f"(d[21]),"+f"(d[22]),"+f"(d[23]),"+f"(d[24]),"+f"(d[25]),"+f"(d[26]),"+f"(d[27]),"+f"(d[28]),"+f"(d[29]),"+f"(d[30]),"+f"(d[31]),"+f"(d[32]),"+f"(d[33]),"+f"(d[34]),"+f"(d[35]),"+f"(d[36]),"+f"(d[37]),"+f"(d[38]),"+f"(d[39]) : "l"(da), "l"(db), "r"(sd));
}
template<> __device__ __forceinline__ void wgmma_rs<16,0>(float* d, uint32_t a0, uint32_t a1, uint32_t a2, uint32_t a3, uint64_t db, int sd) {
  asm volatile("{\n.reg .pred p;\nsetp.ne.b32 p, %13, 0;\n"
  "wgmma.mma_async.sync.aligned.m64n16k16.f32.bf16.bf16 {%0,%1,%2,%3,%4,%5,%6,%7}, {%8,%9,%10,%11}, %12, p, 1, 1, 0;\n}\n"
  : "+f"(d[0]),"+f"(d[1]),"+f"(d[2]),"+f"(d[3]),"+f"(d[4]),"+f"(d[5]),"+f"(d[6]),"+f"(d[7]) : "r"(a0), "r"(a1), "r"(a2), "r"(a3), "l"(db), "r"(sd));
}
template<> __device__ __forceinline__ void wgmma_rs<32,0>(float* d, uint32_t a0, uint32_t a1, uint32_t a2, uint32_t a3, uint64_t db, int sd) {
  asm volatile("{\n.reg .pred p;\nsetp.ne.b32 p, %21, 0;\n"
  "wgmma.mma_async.sync.aligned.m64n32k16.f32.bf16.bf16 {%0,%1,%2,%3,%4,%5,%6,%7,%8,%9,%10,%11,%12,%13,%14,%15}, {%16,%17,%18,%19}, %20, p, 1, 1, 0;\n}\n"
  : "+f"(d[0]),"+f"(d[1]),"+f"(d[2]),"+f"(d[3]),"+f"(d[4]),"+f"(d[5]),"+f"(d[6]),"+f"(d[7]),"+f"(d[8]),"+f"(d[9]),"+f"(d[10]),"+f"(d[11]),"+f"(d[12]),"+f"(d[13]),"+f"(d[14]),"+f"(d[15]) : "r"(a0), "r"(a1), "r"(a2), "r"(a3), "l"(db), "r"(sd));
}
template<> __device__ __forceinline__ void wgmma_rs<48,0>(float* d, uint32_t a0, uint32_t a1, uint32_t a2, uint32_t a3, uint64_t db, int sd) {
  asm volatile("{\n.reg .pred p;\nsetp.ne.b32 p, %29, 0;\n"
  "wgmma.mma_async.sync.aligned.m64n48k16.f32.bf16.bf16 {%0,%1,%2,%3,%4,%5,%6,%7,%8,%9,%10,%11,%12,%13,%14,%15,%16,%17,%18,%19,%20,%21,%22,%23}, {%24,%25,%26,%27}, %28, p, 1, 1, 0;\n}\n"
  : "+f"(d[0]),"+f"(d[1]),"+f"(d[2]),"+f"(d[3]),"+f"(d[4]),"+f"(d[5]),"+f"(d[6]),"+f"(d[7]),"+f"(d[8]),"+f"(d[9]),"+f"(d[10]),"+f"(d[11]),"+f"(d[12]),"+f"(d[13]),"+f"(d[14]),"+f"(d[15]),"+f"(d[16]),"+f"(d[17]),"+f"(d[18]),"+f"(d[19]),"+f"(d[20]),"+f"(d[21]),"+f"(d[22]),"+f"(d[23]) : "r"(a0), "r"(a1), "r"(a2), "r"(a3), "l"(db), "r"(sd));
}
template<> __device__ __forceinline__ void wgmma_rs<64,0>(float* d, uint32_t a0, uint32_t a1, uint32_t a2, uint32_t a3, uint64_t db, int sd) {
  asm volatile("{\n.reg .pred p;\nsetp.ne.b32 p, %37, 0;\n"
  "wgmma.mma_async.sync.aligned.m64n64k16.f32.bf16.bf16 {%0,%1,%2,%3,%4,%5,%6,%7,%8,%9,%10,%11,%12,%13,%14,%15,%16,%17,%18,%19,%20,%21,%22,%23,%24,%25,%26,%27,%28,%29,%30,%31}, {%32,%33,%34,%35}, %36, p, 1, 1, 0;\n}\n"
  : "+f"(d[0]),"+f"(d[1]),"+f"(d[2]),"+f"(d[3]),"+f"(d[4]),"+f"(d[5]),"+f"(d[6]),"+f"(d[7]),"+f"(d[8]),"+f"(d[9]),"+f"(d[10]),"+f"(d[11]),"+f"(d[12]),"+f"(d[13]),"+f"(d[14]),"+f"(d[15]),"+f"(d[16]),"+f"(d[17]),"+f"(d[18]),"+f"(d[19]),"+f"(d[20]),"+f"(d[21]),"+f"(d[22]),"+f"(d[23]),"+f"(d[24]),"+f"(d[25]),"+f"(d[26]),"+f"(d[27]),"+f"(d[28]),"+f"(d[29]),"+f"(d[30]),"+f"(d[31]) : "r"(a0), "r"(a1), "r"(a2), "r"(a3), "l"(db), "r"(sd));
}
template<> __device__ __forceinline__ void wgmma_rs<80,0>(float* d, uint32_t a0, uint32_t a1, uint32_t a2, uint32_t a3, uint64_t db, int sd) {
  asm volatile("{\n.reg .pred p;\nsetp.ne.b32 p, %45, 0;\n"
  "wgmma.mma_async.sync.aligned.m64n80k16.f32.bf16.bf16 {%0,%1,%2,%3,%4,%5,%6,%7,%8,%9,%10,%11,%12,%13,%14,%15,%16,%17,%18,%19,%20,%21,%22,%23,%24,%25,%26,%27,%28,%29,%30,%31,%32,%33,%34,%35,%36,%37,%38,%39}, {%40,%41,%42,%43}, %44, p, 1, 1, 0;\n}\n"
  : "+f"(d[0]),"+f"(d[1]),"+f"(d[2]),"+f"(d[3]),"+f"(d[4]),"+f"(d[5]),"+f"(d[6]),"+f"(d[7]),"+f"(d[8]),"+f"(d[9]),"+f"(d[10]),"+f"(d[11]),"+f"(d[12]),"+f"(d[13]),"+f"(d[14]),"+f"(d[15]),"+f"(d[16]),"+f"(d[17]),"+f"(d[18]),"+f"(d[19]),"+f"(d[20]),"+f"(d[21]),"+f"(d[22]),"+f"(d[23]),"+f"(d[24]),"+f"(d[25]),"+f"(d[26]),"+f"(d[27]),"+f"(d[28]),"+f"(d[29]),"+f"(d[30]),"+f"(d[31]),"+f"(d[32]),"+f"(d[33]),"+f"(d[34]),"+f"(d[35]),"+f"(d[36]),"+f"(d[37]),"+f"(d[38]),"+f"(d[39]) : "r"(a0), "r"(a1), "r"(a2), "r"(a3), "l"(db), "r"(sd));
}
template<> __device__ __forceinline__ void wgmma_rs<96,0>(float* d, uint32_t a0, uint32_t a1, uint32_t a2, uint32_t a3, uint64_t db, int sd) {
  asm volatile("{\n.reg .pred p;\nsetp.ne.b32 p, %53, 0;\n"
  "wgmma.mma_async.sync.aligned.m64n96k16.f32.bf16.bf16 {%0,%1,%2,%3,%4,%5,%6,%7,%8,%9,%10,%11,%12,%13,%14,%15,%16,%17,%18,%19,%20,%21,%22,%23,%24,%25,%26,%27,%28,%29,%30,%31,%32,%33,%34,%35,%36,%37,%38,%39,%40,%41,%42,%43,%44,%45,%46,%47}, {%48,%49,%50,%51}, %52, p, 1, 1, 0;\n}\n"
  : "+f"(d[0]),"+f"(d[1]),"+f"(d[2]),"+f"(d[3]),"+f"(d[4]),"+f"(d[5]),"+f"(d[6]),"+f"(d[7]),"+f"(d[8]),"+f"(d[9]),"+f"(d[10]),"+f"(d[11]),"+f"(d[12]),"+f"(d[13]),"+f"(d[14]),"+f"(d[15]),"+f"(d[16]),"+f"(d[17]),"+f"(d[18]),"+f"(d[19]),"+f"(d[20]),"+f"(d[21]),"+f"(d[22]),"+f"(d[23]),"+f"(d[24]),"+f"(d[25]),"+f"(d[26]),"+f"(d[27]),"+f"(d[28]),"+f"(d[29]),"+f"(d[30]),"+f"(d[31]),"+f"(d[32]),"+f"(d[33]),"+f"(d[34]),"+f"(d[35]),"+f"(d[36]),"+f"(d[37]),"+f"(d[38]),"+f"(d[39]),"+f"(d[40]),"+f"(d[41]),"+f"(d[42]),"+f"(d[43]),"+f"(d[44]),"+f"(d[45]),"+f"(d[46]),"+f"(d[47]) : "r"(a0), "r"(a1), "r"(a2), "r"(a3), "l"(db), "r"(sd));
}
template<> __device__ __forceinline__ void wgmma_rs<112,0>(float* d, uint32_t a0, uint32_t a1, uint32_t a2, uint32_t a3, uint64_t db, int sd) {
  asm volatile("{\n.reg .pred p;\nsetp.ne.b32 p, %61, 0;\n"
  "wgmma.mma_async.sync.aligned.m64n112k16.f32.bf16.bf16 {%0,%1,%2,%3,%4,%5,%6,%7,%8,%9,%10,%11,%12,%13,%14,%15,%16,%17,%18,%19,%20,%21,%22,%23,%24,%25,%26,%27,%28,%29,%30,%31,%32,%33,%34,%35,%36,%37,%38,%39,%40,%41,%42,%43,%44,%45,%46,%47,%48,%49,%50,%51,%52,%53,%54,%55}, {%56,%57,%58,%59}, %60, p, 1, 1, 0;\n}\n"
  : "+f"(d[0]),"+f"(d[1]),"+f"(d[2]),"+f"(d[3]),"+f"(d[4]),"+f"(d[5]),"+f"(d[6]),"+f"(d[7]),"+f"(d[8]),"+f"(d[9]),"+f"(d[10]),"+f"(d[11]),"+f"(d[12]),"+f"(d[13]),"+f"(d[14]),"+f"(d[15]),"+f"(d[16]),"+f"(d[17]),"+f"(d[18]),"+f"(d[19]),"+f"(d[20]),"+f"(d[21]),"+f"(d[22]),"+f"(d[23]),"+f"(d[24]),"+f"(d[25]),"+f"(d[26]),"+f"(d[27]),"+f"(d[28]),"+f"(d[29]),"+f"(d[30]),"+f"(d[31]),"+f"(d[32]),"+f"(d[33]),"+f"(d[34]),"+f"(d[35]),"+f"(d[36]),"+f"(d[37]),"+f"(d[38]),"+f"(d[39]),"+f"(d[40]),"+f"(d[41]),"+f"(d[42]),"+f"(d[43]),"+f"(d[44]),"+f"(d[45]),"+f"(d[46]),"+f"(d[47]),"+f"(d[48]),"+f"(d[49]),"+f"(d[50]),"+f"(d[51]),"+f"(d[52]),"+f"(d[53]),"+f"(d[54]),"+f"(d[55]) : "r"(a0), "r"(a1), "r"(a2), "r"(a3), "l"(db), "r"(sd));
}
template<> __device__ __forceinline__ void wgmma_rs<128,0>(float* d, uint32_t a0, uint32_t a1, uint32_t a2, uint32_t a3, uint64_t db, int sd) {
  asm volatile("{\n.reg .pred p;\nsetp.ne.b32 p, %69, 0;\n"
  "wgmma.mma_async.sync.aligned.m64n128k16.f32.bf16.bf16 {%0,%1,%2,%3,%4,%5,%6,%7,%8,%9,%10,%11,%12,%13,%14,%15,%16,%17,%18,%19,%20,%21,%22,%23,%24,%25,%26,%27,%28,%29,%30,%31,%32,%33,%34,%35,%36,%37,%38,%39,%40,%41,%42,%43,%44,%45,%46,%47,%48,%49,%50,%51,%52,%53,%54,%55,%56,%57,%58,%59,%60,%61,%62,%63}, {%64,%65,%66,%67}, %68, p, 1, 1, 0;\n}\n"
  : "+f"(d[0]),"+f"(d[1]),"+f"(d[2]),"+f"(d[3]),"+f"(d[4]),"+f"(d[5]),"+f"(d[6]),"+f"(d[7]),"+f"(d[8]),"+f"(d[9]),"+f"(d[10]),"+f"(d[11]),"+f"(d[12]),"+f"(d[13]),"+f"(d[14]),"+f"(d[15]),"+f"(d[16]),"+f"(d[17]),"+f"(d[18]),"+f"(d[19]),"+f"(d[20]),"+f"(d[21]),"+f"(d[22]),"+f"(d[23]),"+f"(d[24]),"+f"(d[25]),"+f"(d[26]),"+f"(d[27]),"+f"(d[28]),"+f"(d[29]),"+f"(d[30]),"+f"(d[31]),"+f"(d[32]),"+f"(d[33]),"+f"(d[34]),"+f"(d[35]),"+f"(d[36]),"+f"(d[37]),"+f"(d[38]),"+f"(d[39]),"+f"(d[40]),"+f"(d[41]),"+f"(d[42]),"+f"(d[43]),"+f"(d[44]),"+f"(d[45]),"+f"(d[46]),"+f"(d[47]),"+f"(d[48]),"+f"(d[49]),"+f"(d[50]),"+f"(d[51]),"+f"(d[52]),"+f"(d[53]),"+f"(d[54]),"+f"(d[55]),"+f"(d[56]),"+f"(d[57]),"+f"(d[58]),"+f"(d[59]),"+f"(d[60]),"+f"(d[61]),"+f"(d[62]),"+f"(d[63]) : "r"(a0), "r"(a1), "r"(a2), "r"(a3), "l"(db), "r"(sd));
}

namespace {
typedef __nv_bfloat16 bf16;
constexpr int SB0      = 1024;
constexpr int OFF_S    = 1024;
constexpr int STG      = 49152;
constexpr int STG_TX   = 47104;
constexpr int OFF_PHIK = OFF_S - 128;
constexpr int PHIK_HS  = 10240 + 32;
constexpr int OFF_VB   = OFF_S + 49152;
constexpr int OFF_WO   = OFF_S + 75776;
constexpr int OFF_WOT  = OFF_S + 126976;
constexpr int OFF_PHI  = OFF_S + 147456;
constexpr int OFF_KVB  = OFF_PHI + 12800;
constexpr int KVB_S    = 2592;
constexpr int OFF_U    = OFF_KVB + 28672;
constexpr int OFF_KT   = OFF_U + 8960;
constexpr int OFF_P    = OFF_KT + 16640;
constexpr int OFF_G    = 256;
constexpr int OFF_KX   = OFF_S + 40960;
constexpr int SMEM_BYTES = OFF_P + 16384;
static_assert(SMEM_BYTES <= 232448, "smem");
constexpr int B_FULL = 0, B_EMPTY = 24, B_FULLO = 48, B_EMPTYO = 80, B_WO = 112, B_Y = 120, B_FULLU = 128, B_Z = 152, B_T = 160, B_KX = 168, B_G = 176;
constexpr int C_X = 0, C_Y = 8, C_O = 40, C_DONE = 56, C_NUM = 64;

struct Scratch {
  unsigned char xT[640 * 4096];
  unsigned char y[16 * 640 * 256];
  unsigned char o[16 * 8 * 20480];
  float kv[8 * 2 * 2560];
  float gate[16 * 128];
  unsigned cnt[C_NUM * 32];
};
__device__ __align__(1024) Scratch g_s;
#define STAMPM(i)
#define STAMP(i)
#define STAMPW(i)

#define KP 1
#define KUNR_S "unroll 1"
constexpr int SPIN_MAX = 1 << 22;
__device__ __forceinline__ uint32_t smem_u32(const void* p) { return (uint32_t)__cvta_generic_to_shared(p); }
__device__ __forceinline__ void mbar_init(uint32_t bar, int cnt) { asm volatile("mbarrier.init.shared::cta.b64 [%0], %1;" ::"r"(bar), "r"(cnt)); }
__device__ __forceinline__ void mbar_expect(uint32_t bar, int bytes) { asm volatile("mbarrier.arrive.expect_tx.shared::cta.b64 _, [%0], %1;" ::"r"(bar), "r"(bytes) : "memory"); }
__device__ __forceinline__ void mbar_arrive(uint32_t bar) { asm volatile("mbarrier.arrive.shared::cta.b64 _, [%0];" ::"r"(bar) : "memory"); }
__device__ __forceinline__ void mbar_arrive_cl(uint32_t bar, uint32_t cta) {
  asm volatile("{\n.reg .b32 ra;\nmapa.shared::cluster.u32 ra, %0, %1;\nmbarrier.arrive.shared::cluster.b64 _, [ra];\n}\n" ::"r"(bar), "r"(cta) : "memory");
}
__device__ __forceinline__ bool mbar_try(uint32_t bar, int parity) {
  uint32_t ok;
  asm volatile("{\n.reg .pred p;\nmbarrier.try_wait.parity.shared::cta.b64 p, [%1], %2;\nselp.u32 %0, 1, 0, p;\n}\n" : "=r"(ok) : "r"(bar), "r"(parity) : "memory");
  return ok;
}
__device__ __forceinline__ bool mbar_test(uint32_t bar, int parity) {
  uint32_t ok;
  asm volatile("{\n.reg .pred p;\nmbarrier.test_wait.parity.shared::cta.b64 p, [%1], %2;\nselp.u32 %0, 1, 0, p;\n}\n" : "=r"(ok) : "r"(bar), "r"(parity) : "memory");
  return ok;
}
__device__ __forceinline__ void mbar_wait(uint32_t bar, int parity) {
  int n = 0;
  while (!mbar_try(bar, parity)) { if (++n > SPIN_MAX) __trap(); }
}
__device__ __forceinline__ void mbar_wait_nt(uint32_t bar, int parity) {
  int n = 0;
  while (!mbar_try(bar, parity) && ++n < SPIN_MAX) {}
}
__device__ __forceinline__ unsigned ld_acq(const unsigned* p) { unsigned v; asm volatile("ld.acquire.gpu.global.u32 %0, [%1];" : "=r"(v) : "l"(p) : "memory"); return v; }
__device__ __forceinline__ void poll(const unsigned* p, unsigned target) {
  int n = 0;
  while ((int)(ld_acq(p) - target) < 0) { if (++n > SPIN_MAX) __trap(); }
}
__device__ __forceinline__ void red_rel(unsigned* p) { asm volatile("red.release.gpu.global.add.u32 [%0], 1;" ::"l"(p) : "memory"); }
__device__ __forceinline__ void red_rlx(unsigned* p) { asm volatile("red.relaxed.gpu.global.add.u32 [%0], 1;" ::"l"(p) : "memory"); }
__device__ __forceinline__ void fence_async() { asm volatile("fence.proxy.async.shared::cta;" ::: "memory"); }
__device__ __forceinline__ void fence_lite(uint32_t a) { asm volatile("{.reg .u32 v; .reg .pred p; ld.volatile.shared.u32 v, [%0]; setp.eq.u32 p, v, 0x7fb3c1a5; @p ld.volatile.shared.u32 v, [%0];}" ::"r"(a) : "memory"); }
__device__ __forceinline__ void fence_async_g() { asm volatile("fence.proxy.async.global;" ::: "memory"); }
__device__ __forceinline__ void bar_sync(int id, int n) { asm volatile("bar.sync %0, %1;" ::"r"(id), "r"(n) : "memory"); }
__device__ __forceinline__ void bar_arrive(int id, int n) { asm volatile("bar.arrive %0, %1;" ::"r"(id), "r"(n) : "memory"); }
__device__ __forceinline__ void wg_fence() { asm volatile("wgmma.fence.sync.aligned;" ::: "memory"); }
__device__ __forceinline__ void wg_commit() { asm volatile("wgmma.commit_group.sync.aligned;" ::: "memory"); }
template <int N> __device__ __forceinline__ void wg_wait() { asm volatile("wgmma.wait_group.sync.aligned %0;" ::"n"(N) : "memory"); }
template <int N> __device__ __forceinline__ void reg_fence(float* d) {
#pragma unroll
  for (int i = 0; i < N; i++) asm volatile("" : "+f"(d[i])::"memory");
}
template <int N> __device__ __forceinline__ void reg_fence(uint32_t* d) {
#pragma unroll
  for (int i = 0; i < N; i++) asm volatile("" : "+r"(d[i])::"memory");
}
__device__ __forceinline__ uint64_t mkdesc(uint32_t addr, uint32_t lbo, uint32_t sbo, uint32_t swz) {
  return (uint64_t)((addr >> 4) & 0x3FFF) | ((uint64_t)(lbo >> 4) << 16) | ((uint64_t)(sbo >> 4) << 32) | ((uint64_t)swz << 62);
}
__device__ __forceinline__ uint32_t pack(float lo, float hi) { uint32_t r; asm("cvt.rn.bf16x2.f32 %0, %1, %2;" : "=r"(r) : "f"(hi), "f"(lo)); return r; }
__device__ __forceinline__ float blo(uint32_t v) { return __uint_as_float(v << 16); }
__device__ __forceinline__ float bhi(uint32_t v) { return __uint_as_float(v & 0xFFFF0000u); }
__device__ __forceinline__ float ex2(float x) { float r; asm("ex2.approx.ftz.f32 %0, %1;" : "=f"(r) : "f"(x)); return r; }
__device__ __forceinline__ float rcp(float x) { float r; asm("rcp.approx.ftz.f32 %0, %1;" : "=f"(r) : "f"(x)); return r; }
__device__ __forceinline__ void sts32(uint32_t a, uint32_t v) { asm volatile("st.shared.u32 [%0], %1;" ::"r"(a), "r"(v) : "memory"); }
__device__ __forceinline__ void sts64(uint32_t a, uint32_t x, uint32_t y) { asm volatile("st.shared.v2.u32 [%0], {%1,%2};" ::"r"(a), "r"(x), "r"(y) : "memory"); }
__device__ __forceinline__ void sts128(uint32_t a, uint32_t x, uint32_t y, uint32_t z, uint32_t w) { asm volatile("st.shared.v4.u32 [%0], {%1,%2,%3,%4};" ::"r"(a), "r"(x), "r"(y), "r"(z), "r"(w) : "memory"); }
__device__ __forceinline__ uint32_t lds32(uint32_t a) { uint32_t v; asm volatile("ld.shared.u32 %0, [%1];" : "=r"(v) : "r"(a) : "memory"); return v; }
__device__ __forceinline__ uint32_t lds16(uint32_t a) { uint16_t v; asm volatile("ld.shared.u16 %0, [%1];" : "=h"(v) : "r"(a) : "memory"); return v; }
__device__ __forceinline__ uint4 lds128(uint32_t a) { uint4 v; asm volatile("ld.shared.v4.u32 {%0,%1,%2,%3}, [%4];" : "=r"(v.x), "=r"(v.y), "=r"(v.z), "=r"(v.w) : "r"(a) : "memory"); return v; }
__device__ __forceinline__ float4 lds128f(uint32_t a) { float4 v; asm volatile("ld.shared.v4.f32 {%0,%1,%2,%3}, [%4];" : "=f"(v.x), "=f"(v.y), "=f"(v.z), "=f"(v.w) : "r"(a) : "memory"); return v; }
__device__ __forceinline__ void stsm4(uint32_t a, uint32_t r0, uint32_t r1, uint32_t r2, uint32_t r3) { asm volatile("stmatrix.sync.aligned.m8n8.x4.shared.b16 [%0], {%1,%2,%3,%4};" ::"r"(a), "r"(r0), "r"(r1), "r"(r2), "r"(r3) : "memory"); }
__device__ __forceinline__ void stsm4t(uint32_t a, uint32_t r0, uint32_t r1, uint32_t r2, uint32_t r3) { asm volatile("stmatrix.sync.aligned.m8n8.x4.trans.shared.b16 [%0], {%1,%2,%3,%4};" ::"r"(a), "r"(r0), "r"(r1), "r"(r2), "r"(r3) : "memory"); }
__device__ __forceinline__ uint4 ldsm4t(uint32_t a) { uint4 v; asm volatile("ldmatrix.sync.aligned.m8n8.x4.trans.shared.b16 {%0,%1,%2,%3}, [%4];" : "=r"(v.x), "=r"(v.y), "=r"(v.z), "=r"(v.w) : "r"(a) : "memory"); return v; }
__device__ __forceinline__ void tma2d(uint32_t dst, const CUtensorMap* m, int c0, int c1, uint32_t bar) {
  asm volatile("cp.async.bulk.tensor.2d.shared::cluster.global.mbarrier::complete_tx::bytes [%0], [%1, {%3,%4}], [%2];" ::"r"(dst), "l"(m), "r"(bar), "r"(c0), "r"(c1) : "memory");
}
__device__ __forceinline__ void tma3d_mc(uint32_t dst, const CUtensorMap* m, int c0, int c1, int c2, uint32_t bar) {
  asm volatile("cp.async.bulk.tensor.3d.shared::cluster.global.mbarrier::complete_tx::bytes.multicast::cluster [%0], [%1, {%3,%4,%5}], [%2], %6;" ::"r"(dst), "l"(m), "r"(bar), "r"(c0), "r"(c1), "r"(c2), "h"((uint16_t)3) : "memory");
}
__device__ __forceinline__ void tma5d(uint32_t dst, const CUtensorMap* m, int c0, int c1, int c2, int c3, int c4, uint32_t bar) {
  asm volatile("cp.async.bulk.tensor.5d.shared::cluster.global.mbarrier::complete_tx::bytes [%0], [%1, {%3,%4,%5,%6,%7}], [%2];" ::"r"(dst), "l"(m), "r"(bar), "r"(c0), "r"(c1), "r"(c2), "r"(c3), "r"(c4) : "memory");
}
__device__ __forceinline__ void bulk_ld(uint32_t dst, const void* src, int bytes, uint32_t bar) {
  asm volatile("cp.async.bulk.shared::cluster.global.mbarrier::complete_tx::bytes [%0], [%1], %2, [%3];" ::"r"(dst), "l"(src), "r"(bytes), "r"(bar) : "memory");
}
__device__ __forceinline__ void bulk_ld_mc(uint32_t dst, const void* src, int bytes, uint32_t bar) {
  asm volatile("cp.async.bulk.shared::cluster.global.mbarrier::complete_tx::bytes.multicast::cluster [%0], [%1], %2, [%3], %4;" ::"r"(dst), "l"(src), "r"(bytes), "r"(bar), "h"((uint16_t)3) : "memory");
}
__device__ __forceinline__ void tma_st2d(const CUtensorMap* m, uint32_t src, int c0, int c1) {
  asm volatile("cp.async.bulk.tensor.2d.global.shared::cta.bulk_group [%0, {%2,%3}], [%1];" ::"l"(m), "r"(src), "r"(c0), "r"(c1) : "memory");
}
__device__ __forceinline__ void red4(float* p, float a, float b, float c) { asm volatile("red.relaxed.gpu.global.add.v4.f32 [%0], {%1,%2,%3,%4};" ::"l"(p), "f"(a), "f"(b), "f"(c), "f"(1.f) : "memory"); }
__device__ __forceinline__ float4 ld_rlx4(const float* p) { float4 v; asm volatile("ld.relaxed.gpu.global.v4.f32 {%0,%1,%2,%3}, [%4];" : "=f"(v.x), "=f"(v.y), "=f"(v.z), "=f"(v.w) : "l"(p) : "memory"); return v; }
__device__ __forceinline__ unsigned ld_rlx(const unsigned* p) { unsigned v; asm volatile("ld.relaxed.gpu.global.u32 %0, [%1];" : "=r"(v) : "l"(p) : "memory"); return v; }
__device__ __forceinline__ uint32_t mapa(uint32_t a, uint32_t cta) { uint32_t r; asm("mapa.shared::cluster.u32 %0, %1, %2;" : "=r"(r) : "r"(a), "r"(cta)); return r; }
__device__ __forceinline__ void st_async4(uint32_t a, float x, float y, float z, float w, uint32_t bar) {
  asm volatile("st.async.weak.shared::cluster.mbarrier::complete_tx::bytes.v4.f32 [%0], {%1,%2,%3,%4}, [%5];" ::"r"(a), "f"(x), "f"(y), "f"(z), "f"(w), "r"(bar) : "memory");
}
__device__ __forceinline__ void cl_arrive() { asm volatile("barrier.cluster.arrive.relaxed.aligned;" ::: "memory"); }
__device__ __forceinline__ void cl_wait() { asm volatile("barrier.cluster.wait.acquire.aligned;" ::: "memory"); }
__device__ __forceinline__ float bf2f(uint16_t v) { return __uint_as_float((uint32_t)v << 16); }
__device__ __forceinline__ float rbf(float x) { return __bfloat162float(__float2bfloat16_rn(x)); }

#define WIDE 1e18f
constexpr float LOG2E = 1.4426950408889634f;
__device__ __forceinline__ float softmax_row(const float* p, uint32_t* ph) {
  float mx = fmaxf(p[0], p[1]);
#pragma unroll
  for (int j = 1; j < 10; j++) mx = fmaxf(mx, fmaxf(p[4 * j], p[4 * j + 1]));
  const float mxl = -mx * LOG2E;
  float e[20], q[10], s0 = 0.f, s1 = 0.f;
#pragma unroll
  for (int j = 0; j < 10; j++) {
    e[2 * j] = ex2(fmaf(p[4 * j], LOG2E, mxl));
    e[2 * j + 1] = ex2(fmaf(p[4 * j + 1], LOG2E, mxl));
    const float u = e[2 * j] + e[2 * j + 1];
    q[j] = rcp(e[2 * j] * e[2 * j + 1]);
    s0 += u; s1 = fmaf(q[j], u, s1);
  }
  const float rs = rcp(s0), rn = rcp(s1);
#pragma unroll
  for (int j = 0; j < 10; j++) {
    ph[j] = pack(e[2 * j] * rs, e[2 * j + 1] * rs);
    const float c = q[j] * rn;
    ph[10 + j] = pack(e[2 * j + 1] * c, e[2 * j] * c);
  }
  return s1;
}
__device__ __forceinline__ bool softmax_wide(float chk) { return __builtin_expect(!(chk < WIDE), 0); }
__device__ __forceinline__ void softmax_neg(const float* p, uint32_t* ph) {
  float mn = fminf(p[0], p[1]);
#pragma unroll
  for (int j = 1; j < 10; j++) mn = fminf(mn, fminf(p[4 * j], p[4 * j + 1]));
  const float mnl = mn * LOG2E;
  float e[20], s = 0.f;
#pragma unroll
  for (int j = 0; j < 10; j++) {
    e[2 * j] = ex2(fmaf(p[4 * j], -LOG2E, mnl));
    e[2 * j + 1] = ex2(fmaf(p[4 * j + 1], -LOG2E, mnl));
    s += e[2 * j] + e[2 * j + 1];
  }
  const float rf = rcp(s);
#pragma unroll
  for (int j = 0; j < 10; j++) ph[10 + j] = pack(e[2 * j] * rf, e[2 * j + 1] * rf);
}

struct cf { float x, y; };
__device__ __forceinline__ cf cexpp(float a2, float be, float p) {
  float m = ex2(a2 * p), th = be * p;
  return cf{m * __cosf(th), m * __sinf(th)};
}
__device__ __forceinline__ cf cmul(cf a, cf b) { return cf{fmaf(a.x, b.x, -a.y * b.y), fmaf(a.x, b.y, a.y * b.x)}; }

__device__ __forceinline__ uint32_t prmt(uint32_t a, uint32_t b, uint32_t s) { uint32_t r; asm("prmt.b32 %0, %1, %2, %3;" : "=r"(r) : "r"(a), "r"(b), "r"(s)); return r; }
template <int P> __device__ __forceinline__ void conv_ld(uint32_t ka, uint32_t* a) {
#pragma unroll
  for (int h = 0; h < 4; h++)
    asm volatile("ld.shared.v2.u32 {%0,%1}, [%2];" : "=r"(a[2 * h]), "=r"(a[2 * h + 1]) : "r"(ka - 256 * (2 * P + (h >> 1)) + 8 * (h & 1)) : "memory");
}
template <int P> struct ConvLoop {
  static __device__ __forceinline__ void run(float* acc, uint32_t ka, uint64_t db, uint32_t (*a)[8]) {
    uint32_t* c = a[P & 3];
    wg_fence();
    wgmma_rs<128 - 16 * (P / 2), 0>(acc, c[0], c[1], c[2], c[3], db + 8 * P, 1);
    wgmma_rs<128 - 16 * (P / 2), 0>(acc, c[4], c[5], c[6], c[7], db + 8 * P + 4, 1);
    wg_commit();
    if (P < 14) {
      if (P >= 2) wg_wait<2>();
      conv_ld<P + 2>(ka, a[(P + 2) & 3]);
    }
    ConvLoop<P + 1>::run(acc, ka, db, a);
  }
};
template <> struct ConvLoop<16> { static __device__ __forceinline__ void run(float*, uint32_t, uint64_t, uint32_t (*)[8]) {} };

__device__ __forceinline__ uint32_t hmul(uint32_t a, uint32_t b) { uint32_t r; asm("mul.rn.bf16x2 %0, %1, %2;" : "=r"(r) : "r"(a), "r"(b)); return r; }
__device__ __forceinline__ uint32_t hfma(uint32_t a, uint32_t b, uint32_t c) { uint32_t r; asm("fma.rn.bf16x2 %0, %1, %2, %3;" : "=r"(r) : "r"(a), "r"(b), "r"(c)); return r; }
__device__ __forceinline__ uint32_t hadd(uint32_t a, uint32_t b) { uint32_t r; asm("add.rn.bf16x2 %0, %1, %2;" : "=r"(r) : "r"(a), "r"(b)); return r; }
struct c2 { uint32_t x, y; };
struct cd { uint32_t x, y, n; };
__device__ __forceinline__ c2 pk2(cf a, cf b) { return c2{pack(a.x, b.x), pack(a.y, b.y)}; }
__device__ __forceinline__ cd dup(cf a) { return cd{pack(a.x, a.x), pack(a.y, a.y), pack(-a.y, -a.y)}; }
__device__ __forceinline__ c2 cmul2(cd a, c2 b) { return c2{hfma(a.x, b.x, hmul(a.n, b.y)), hfma(a.x, b.y, hmul(a.y, b.x))}; }
__device__ __forceinline__ void sts_c2(uint32_t a, c2 p, c2 q, c2 r, c2 u) { sts128(a, p.x, q.x, r.x, u.x); sts128(a + 128, p.y, q.y, r.y, u.y); }
__device__ __forceinline__ cf csq(cf a) { return cf{fmaf(a.x, a.x, -a.y * a.y), (a.x + a.x) * a.y}; }
__device__ __forceinline__ void sts16(uint32_t a, uint32_t v) { asm volatile("st.shared.u16 [%0], %1;" ::"r"(a), "h"((uint16_t)v) : "memory"); }

__device__ __forceinline__ void put_compact(uint32_t kv, int th, const uint32_t* r) {
  const int i = th >> 2, t = th & 3;
  sts32(kv + th * 4, r[0]);
  sts32(kv + (t < 2 ? 256 + 4 * i + 2 * t : 256 + 64 * t + 2 * i) * 2, r[1]);
  if (t < 2 || th == 2) sts16(kv + (512 + 64 * t + i) * 2, r[2]);
  if (t < 2) sts16(kv + (544 + 64 * t + i) * 2, r[2] >> 16);
}
__device__ __forceinline__ int kblock(int q, int cg) {
  const int kv = 8 + (cg >> 2), pb = KP + (cg >= KP);
  int kb = q + KP - 1 - pb;
  if (cg >= KP && kb >= cg) kb++;
  if (kb >= kv) kb++;
  if (q == pb) kb = kv;
  if (q < pb) kb = q < KP ? q : cg;
  return kb;
}

struct Params {
  Scratch* s;
  const uint16_t *wo, *lar, *aim, *cre, *cim, *ldt, *dsk;
  const uint32_t* wphi;
  const uint16_t* gw;
  const uint4 *x, *w;
};

__global__ void __cluster_dims__(2, 1, 1) __launch_bounds__(512, 1)
fused_kernel(const __grid_constant__ Params prm, const __grid_constant__ CUtensorMap tmX, const __grid_constant__ CUtensorMap tmW,
             const __grid_constant__ CUtensorMap tmWt, const __grid_constant__ CUtensorMap tmWo,
             const __grid_constant__ CUtensorMap tmOut) {
  extern __shared__ __align__(1024) unsigned char smem_raw[];
  const uint32_t sb = smem_u32(smem_raw);
  const int tid = threadIdx.x, lane = tid & 31;
  const int warp = __shfl_sync(0xffffffffu, tid >> 5, 0);
  const int g = lane >> 2, t = lane & 3;
  const int cta = blockIdx.x, rank = cta & 1, cl = cta >> 1;
  const int cg = cl & 7, rt = 2 * (cl >> 3) + rank;
  const int rt3 = 2 * (cl >> 3) + (cg & 1), ct3 = (cg & 6) + rank;
  unsigned* const cnt = prm.s->cnt;
  const int wgid = warp >> 2, th = tid & 127;
  uint32_t n_par[4][4], n_ldt, n_dsk;
  if (!(wgid & 1)) {
    const uint32_t kq = cta * 640 + (wgid ? 0 : 128) + th;
    n_par[0][0] = __ldg(prm.lar + kq); n_par[0][1] = __ldg(prm.aim + kq); n_par[0][2] = __ldg(prm.cre + kq); n_par[0][3] = __ldg(prm.cim + kq);
    const uint32_t cq = 5 * cta + (lane & 3) + ((lane & 3) || !wgid);
    n_ldt = __ldg(prm.ldt + cq); n_dsk = __ldg(prm.dsk + cq);
    if (wgid) {
#pragma unroll
      for (int p = 1; p < 4; p++) {
        const uint32_t q = kq + 128 + 128 * p;
        n_par[p][0] = __ldg(prm.lar + q); n_par[p][1] = __ldg(prm.aim + q); n_par[p][2] = __ldg(prm.cre + q); n_par[p][3] = __ldg(prm.cim + q);
      }
    }
    cl_arrive();
  }
  asm volatile("" ::: "memory");
  if (__shfl_sync(0xffffffffu, tid & 128, 0)) {
    const int iw = (warp & 3) + (wgid & 2) * 2, it = 32 * iw + lane;
    uint32_t wv[4];
#pragma unroll
    for (int i = 0; i < 4; i++) { int idx = it + 256 * i; wv[i] = idx < 800 ? __ldg(prm.wphi + cg * 800 + idx) : 0u; }
    const uint32_t gw0 = __ldg(prm.gw + 64 * kblock(iw >> 1, cg) + (it & 63)), gw1 = __ldg(prm.gw + 128 + it), gw2 = __ldg(prm.gw + 384 + it), gw3 = __ldg(prm.gw + 64 + it);
    if (lane == 0) {
      mbar_init(sb + 8 * iw, iw >= 3 && iw < 6 ? 16 : 1);
      mbar_init(sb + 64 + 8 * iw, iw == 6 ? 4 : iw >= 2 && iw < 6 ? 16 : 1);
      mbar_init(sb + 128 + 8 * iw, iw == 3 ? 3 : 1);
      asm volatile("fence.mbarrier_init.release.cluster;" ::: "memory");
      if (iw < 3) {
        mbar_expect(sb + 8 * iw, STG_TX);
        asm volatile("prefetch.tensormap [%0];" ::"l"((const char*)&tmX + 128 * iw) : "memory");
      }
      if (iw == 5) mbar_expect(sb + B_KX, 7680);
      if ((sb & 0xFFFFFF) != SB0) __trap();
    }
    __syncwarp();
    cl_arrive();
    if (warp == 12) STAMPW(110);
    cl_wait();
    if (warp == 12) {
      STAMPW(112);
      if (lane == 0) {
#pragma unroll 1
        for (int q = 0; q < 3; q++) {
          const uint32_t st = sb + OFF_S + ((3 - q) % 3) * STG, bar = sb + B_FULL + 8 * q;
          const int k0 = 64 * kblock(q, cg);
          tma3d_mc(st + 16384 + rank * 16384, &tmW, 80 * cg, k0 + 32 * rank, 0, bar);
          tma2d(st, &tmX, k0, 128 * rt, bar);
          tma3d_mc(st + 16384 + rank * 16384 + 12288, &tmWt, 80 * cg + 64, k0 + 32 * rank, 0, bar);
        }
      }
      __syncwarp();
      STAMPW(64);
    }
#pragma unroll
    for (int i = 0; i < 4; i++) {
      const int idx = it + 256 * i, kk = idx / 10, j = idx - kk * 10, h = kk / 20;
      if (idx < 800) sts128(sb + OFF_PHI + j * 1280 + kk * 16, h == 0 ? wv[i] : 0u, h == 1 ? wv[i] : 0u, h == 2 ? wv[i] : 0u, h == 3 ? wv[i] : 0u);
    }
    const uint32_t ga = sb + OFF_S + (iw & 1) * 16384 + 31744 + lane * 32 + (lane & 4) * 4;
    if (iw < 6) sts16(ga + ((3 - (iw >> 1)) % 3) * STG, gw0);
    sts16((ga ^ 16) + (iw & 6), gw1); sts16((ga ^ 16) + (iw & 6) + 8, gw2);
    if (iw < 2) sts16((ga ^ 16) + STG, gw3);
    fence_lite(sb + B_T);
    bar_arrive(1, 384);
    bar_sync(2, 256);
  }

  uint32_t kr[9];
#pragma unroll
  for (int i = 0; i < 9; i++) kr[i] = tid;
  if (!(wgid & 1)) {
    const uint32_t sa = sb + (wgid ? OFF_KVB : OFF_P);
    const uint32_t sq = sb + (wgid ? OFF_KVB + 16384 : OFF_KT);
    const uint32_t ea = ((th & 63) >> 3) * 256 + (th & 7) * 16;
    const uint32_t dd = (pack(0.f, expf(blo(n_ldt))) & 0xFFFF0000u) | n_dsk;
#pragma unroll 1
    for (int pass = 0;; pass++) {
      const uint32_t dp = __shfl_sync(0xffffffffu, dd, pass);
      const float dt = bhi(dp), dsk = blo(dp);
      const float a2 = -rbf(expf(blo(n_par[0][0]))) * dt * 1.4426950408889634f, be = blo(n_par[0][1]) * dt;
      cf S = cf{2.f * (blo(n_par[0][2]) * dt), -2.f * (blo(n_par[0][3]) * dt)};
      cf z[9];
      z[1] = cexpp(a2, be, 1.f);
      const cf z64 = cexpp(a2, be, 64.f);
      z[2] = csq(z[1]); z[3] = cmul(z[2], z[1]); z[4] = csq(z[2]);
      z[5] = cmul(z[4], z[1]); z[6] = csq(z[3]); z[7] = cmul(z[4], z[3]); z[8] = csq(z[4]);
      const uint32_t ba = sq + ea + (th >> 6) * 6144;
      sts128(ba, pack(1.f, z[1].x), pack(z[2].x, z[3].x), pack(z[4].x, z[5].x), pack(z[6].x, z[7].x));
      sts128(ba + 128, pack(0.f, z[1].y), pack(z[2].y, z[3].y), pack(z[4].y, z[5].y), pack(z[6].y, z[7].y));
      {
        const cf z256 = csq(csq(z64)), z512 = csq(z256), z768 = cmul(z512, z256), z1024 = csq(z512);
        const cf a = cmul(z256, z[2]), b = cmul(z256, z[4]), c = cmul(z256, z[6]), d = cmul(z512, z[4]), f = cmul(z768, z[4]);
        sts128(ba + 2048, pack(z256.x, a.x), pack(b.x, c.x), pack(z512.x, d.x), pack(z768.x, f.x));
        sts128(ba + 2048 + 128, pack(z256.y, a.y), pack(b.y, c.y), pack(z512.y, d.y), pack(z768.y, f.y));
        const cf p = cmul(z1024, z256), q = csq(z768), r = cmul(z1024, z768), u = csq(z1024);
        sts128(ba + 4096, pack(z1024.x, p.x), pack(q.x, r.x), pack(u.x, 0.f), 0);
        sts128(ba + 4096 + 128, pack(z1024.y, p.y), pack(q.y, r.y), pack(u.y, 0.f), 0);
      }
      cf T[8];
      T[1] = cf{z[8].x, -z[8].y}; T[2] = csq(T[1]); T[3] = cmul(T[2], T[1]); T[4] = csq(T[2]);
      T[5] = cmul(T[4], T[1]); T[6] = csq(T[3]); T[7] = cmul(T[4], T[3]);
      const uint32_t aa = sa + ea + (th >> 6) * 2048;
      const c2 t0 = pk2(cf{1.f, 0.f}, T[1]), t1 = pk2(T[2], T[3]), t2 = pk2(T[4], T[5]), t3 = pk2(T[6], T[7]);
#pragma unroll
      for (int c = 0; c < 4; c++) {
        const cd sd = dup(S);
        if (c < 3) S = cmul(S, cf{z64.x, -z64.y});
        sts_c2(aa + 4096 * c, cmul2(sd, t0), cmul2(sd, t1), cmul2(sd, t2), cmul2(sd, t3));
      }
      if ((warp & 3) == 0 && pass == 0) STAMPW(227 - (wgid >> 1));
      fence_lite(sb + B_T);
      bar_sync(10 - (wgid >> 1), 128);
      float kc[24];
      const uint64_t da = mkdesc(sa, 128, 2048, 0), db = mkdesc(sq, 128, 2048, 0);
      wg_fence();
#pragma unroll
      for (int s = 0; s < 8; s++) wgmma_ss<48, 1, 1>(kc, da + 16 * s, db + 16 * s, s > 0);
      wg_commit();
      if (pass == 0) cl_wait();
      wg_wait<0>();
      reg_fence<24>(kc);
#pragma unroll
      for (int i = 0; i < 6; i++) kr[i] = kr[i + 3];
      kr[6] = pack(kc[0] + kc[14] + (th == 0 ? dsk : 0.f), kc[1] + kc[15]);
      kr[7] = pack(kc[4] + kc[18], kc[5] + kc[19]);
      kr[8] = pack(kc[8] + kc[22], kc[9] + kc[23]);
      if (pass == 0) put_compact(sb + OFF_U + (wgid ? 0 : 4480), th, kr + 6);
      if ((warp & 3) == 0) STAMPW(231 - (wgid >> 1) + 4 * pass);
      if (wgid == 0) { bar_arrive(3, 192); bar_sync(1, 384); break; }
      if (pass == 3) { bar_arrive(12, 192); break; }
      bar_sync(4, 128);
      if (pass == 0) bar_arrive(11, 192);
#pragma unroll
      for (int i = 0; i < 4; i++) n_par[0][i] = pass == 0 ? n_par[1][i] : pass == 1 ? n_par[2][i] : n_par[3][i];
    }
  }

  if (warp < 8) {
    const int wg = warp >> 2, w = warp & 3;
    uint32_t raA, raB;
    uint32_t oA, oB;
    {
      const int tt = (lane >> 1) & 3, row = 64 * ((warp >> 1) & 1) + 16 * tt + 4 * (lane >> 3) + 2 * wg + (lane & 1);
      const int sA = (cg < KP ? cg : KP) % 3, sB = (KP + (cg >= KP)) % 3;
      raA = sb + OFF_S + ((3 - sA) % 3) * STG + row * 128 + (((warp & 1) ^ (2 * tt) ^ (row & 7)) * 16);
      oA = ((64 * cg + 8 * (warp & 1) + g) * 4096 + wg * 2048 + (127 - 8 * rt - 4 * ((warp >> 1) & 1) - t) * 16);
      const int rowb = 32 * (cg & 3) + 16 * (tt & 1) + 4 * (lane >> 3) + (tt & 2) + (lane & 1);
      raB = sb + OFF_S + ((3 - sB) % 3) * STG + rowb * 128 + ((warp ^ (rowb & 7)) * 16);
      oB = ((512 + 64 * (cg >> 2) + 8 * warp + g) * 4096 + (t >> 1) * 2048 + (127 - 8 * rt - 2 * (cg & 3) - (t & 1)) * 16);
      asm volatile("" : "+r"(raA), "+r"(raB), "+r"(oA), "+r"(oB));
    }
    asm volatile("setmaxnreg.inc.sync.aligned.u32 168;");
    {
    int lane;
    asm volatile("mov.u32 %0, %%laneid;" : "=r"(lane));
    const int g = lane >> 2, t = lane & 3;
    float acc[124];
#pragma unroll
    for (int i = 0; i < 124; i++) acc[i] = 0.f;
    reg_fence<124>(acc);
    STAMPW(0 + warp);
    int pA = cg < KP ? cg : KP, pB = KP + (cg >= KP);
    asm volatile("" : "+r"(pA), "+r"(pB));
    const uint32_t eb = mapa(sb + B_EMPTY, lane & 1);
    uint32_t so = 0, fb = sb + B_FULL, par = 0, eo = 16;
    const uint32_t la0 = ((SB0 + OFF_S) >> 4) + (1 << 16) + wg * 512;
#pragma unroll 1
    for (int kb = 0; kb < 10; kb++) {
      bool rel = kb > 0 && lane < 2;
      if (!__all_sync(0xffffffffu, mbar_test(fb, par))) {
        wg_wait<0>();
        if (rel) asm volatile("mbarrier.arrive.shared::cluster.b64 _, [%0];" ::"r"(eb + eo) : "memory");
        rel = false;
        mbar_wait_nt(fb, par);
      }
      if (warp == 0) STAMPM(40 + kb);
      if (warp == 4) STAMPM(130 + kb);
      const uint64_t da = 0x4000004000000000ull | (la0 + so);
      const uint64_t db = 0x4000004000000000ull | (((SB0 + OFF_S + 16384) >> 4) + (256 << 16) + so);
      const uint64_t dt = 0xC000001000000000ull | (((SB0 + OFF_S + 28672) >> 4) + (64 << 16) + so);
      wg_fence();
#pragma unroll
      for (int ks = 0; ks < 2; ks++) {
        wgmma_ss<192, 0, 1>(acc, da + 2 * ks, db + ks * 128, 1);
        wgmma_ss<56, 0, 1>(acc + 96, da + 2 * ks, dt + ks * 32, 1);
      }
      wg_commit();
      wg_wait<1>();
      if (rel) asm volatile("mbarrier.arrive.shared::cluster.b64 _, [%0];" ::"r"(eb + eo) : "memory");
      if (w == 0) STAMPM(159 + 10 * wg + kb);
      wg_fence();
#pragma unroll
      for (int ks = 0; ks < 2; ks++) {
        wgmma_ss<192, 0, 1>(acc, da + 4 + 2 * ks, db + 1024 + ks * 128, 1);
        wgmma_ss<56, 0, 1>(acc + 96, da + 4 + 2 * ks, dt + 1024 + ks * 32, 1);
      }
      wg_commit();
      if (w == 0) STAMPM(140 + 10 * wg + kb);
      if (so == STG / 16) { fb -= 16; par ^= 1; } else fb += 8;
      eo = eo == 16 ? 0 : eo + 8;
      so = so == 0 ? 2 * STG / 16 : so - STG / 16;
      if (kb == pA) {
        uint4 v0 = ldsm4t(raA), v1 = ldsm4t(raA ^ 32), v2 = ldsm4t(raA ^ 64), v3 = ldsm4t(raA ^ 96);
        if (t & 1) { uint4 u = v0; v0 = v1; v1 = u; u = v2; v2 = v3; v3 = u; }
        if (t & 2) { uint4 u = v0; v0 = v2; v2 = u; u = v1; v1 = v3; v3 = u; }
        unsigned char* dsA = prm.s->xT + oA;
        __stcg((uint4*)dsA, v0); __stcg((uint4*)(dsA + 65536), v1); __stcg((uint4*)(dsA + 131072), v2); __stcg((uint4*)(dsA + 196608), v3);
      } else if (kb == pB) {
        __stcg((uint4*)(prm.s->xT + oB), ldsm4t(raB));
        bar_arrive(8, 288);
      }
    }
    wg_wait<0>();
    if (lane < 2) mbar_arrive_cl(sb + B_EMPTY, lane);
    if (w == 0) STAMPM(169 + 10 * wg);
    reg_fence<124>(acc);
    STAMPW(8 + warp);
    uint32_t ph0[20], ph1[20];
    float pq[40];
    {
      float pk[40];
      const uint64_t dphi = mkdesc(sb + OFF_PHI, 128, 1280, 0);
      const uint32_t rg = (8 * wg + 2 * w) * 128;
      mbar_wait(sb + B_EMPTY + 16, 0);
      {
        uint32_t va[20];
#pragma unroll
        for (int j = 0; j < 10; j++) {
          const int bv = j < 8 ? 16 + j : 20 + j;
          va[2 * j] = pack(acc[4 * bv], acc[4 * bv + 1]); va[2 * j + 1] = pack(acc[4 * bv + 2], acc[4 * bv + 3]);
        }
        const uint32_t v0 = sb + OFF_VB + rg + (lane & 15) * 16;
        const uint32_t hi = lane >> 4;
        stsm4(v0 + (0 + hi) * 2048, va[0], va[1], va[2], va[3]);
        stsm4(v0 + (3 + hi) * 2048, va[4], va[5], va[6], va[7]);
        stsm4(v0 + (5 + hi) * 2048, va[8], va[9], va[10], va[11]);
        stsm4(v0 + (7 + 2 * hi) * 2048, va[12], va[13], va[14], va[15]);
        stsm4(v0 + (10 + hi) * 2048, va[16], va[17], va[18], va[19]);
        sts128(v0 + (2 + 6 * hi) * 2048, 0x3F803F80u, 0x3F803F80u, 0x3F803F80u, 0x3F803F80u);
      }
      uint32_t fq[20];
#pragma unroll
      for (int j = 0; j < 10; j++) {
        const int bq = j < 8 ? j : 16 + j;
        fq[2 * j] = pack(acc[4 * bq], acc[4 * bq + 1]); fq[2 * j + 1] = pack(acc[4 * bq + 2], acc[4 * bq + 3]);
      }
      uint32_t fa[20];
#pragma unroll
      for (int j = 0; j < 10; j++) {
        const int bk = j < 8 ? 8 + j : 18 + j;
        fa[2 * j] = pack(acc[4 * bk], acc[4 * bk + 1]); fa[2 * j + 1] = pack(acc[4 * bk + 2], acc[4 * bk + 3]);
      }
      reg_fence<20>(fa); reg_fence<20>(fq);
      wg_fence();
#pragma unroll
      for (int s = 0; s < 5; s++) wgmma_rs<80, 1>(pk, fa[4 * s], fa[4 * s + 1], fa[4 * s + 2], fa[4 * s + 3], dphi + 16 * s, s > 0);
      wg_commit();
#pragma unroll
      for (int s = 0; s < 5; s++) wgmma_rs<80, 1>(pq, fq[4 * s], fq[4 * s + 1], fq[4 * s + 2], fq[4 * s + 3], dphi + 16 * s, s > 0);
      wg_commit();
      wg_wait<1>();
      reg_fence<40>(pk);
      if (warp == 0) STAMPW(66);
      if (rank == (cg & 1) && t == 0) {
#pragma unroll
        for (int r = 0; r < 2; r++)
          asm volatile("st.async.weak.shared::cluster.mbarrier::complete_tx::bytes.v2.f32 [%0], {%1,%2}, [%3];" ::"r"(mapa(sb + OFF_G + warp * 64 + g * 8, r)), "f"(acc[120]), "f"(acc[122]), "r"(mapa(sb + B_G, r)) : "memory");
      }
      float chk = softmax_row(pk, ph0);
      mbar_wait(sb + B_EMPTY, 1);
      const uint32_t a0 = sb + OFF_PHIK + t * PHIK_HS + rg + g * 16;
#pragma unroll
      for (int c = 0; c < 5; c++) sts128(a0 + c * 2048, ph0[4 * c], ph0[4 * c + 1], ph0[4 * c + 2], ph0[4 * c + 3]);
      chk += softmax_row(pk + 2, ph1);
#pragma unroll
      for (int c = 0; c < 5; c++) sts128(a0 + c * 2048 + 128, ph1[4 * c], ph1[4 * c + 1], ph1[4 * c + 2], ph1[4 * c + 3]);
      if (softmax_wide(chk)) {
#pragma unroll
        for (int r = 0; r < 2; r++) {
          softmax_neg(pk + 2 * r, ph0);
#pragma unroll
          for (int c = 5; c < 10; c++) sts64(a0 + (c >> 1) * 2048 + (c & 1) * 8 + 128 * r, ph0[2 * c], ph0[2 * c + 1]);
        }
      }
    }
    fence_lite(sb + B_T);
    bar_sync(1, 256);
    STAMPW(16 + warp);
    {
      float kv[32];
      wg_fence();
#pragma unroll
      for (int hh = 0; hh < 2; hh++) {
        const uint64_t da = mkdesc(sb + OFF_PHIK + (2 * wg + hh) * PHIK_HS, 128, 2048, 0);
        const uint64_t db = mkdesc(sb + OFF_VB + (6 * wg + 2 * hh) * 2048, 128, 2048, 0);
#pragma unroll
        for (int s = 0; s < 8; s++) wgmma_ss<32, 1, 1>(kv + 16 * hh, da + 16 * s, db + 16 * s, s > 0);
      }
      wg_commit();
      mbar_wait(sb + B_Z, 0);
      wg_wait<0>();
      reg_fence<32>(kv);
      reg_fence<40>(pq);
      if (warp == 0) STAMPW(67);
      if (w < 3) {
        float v[2][12];
#pragma unroll
        for (int r = 0; r < 2; r++) {
          v[r][0] = kv[2 * r]; v[r][1] = kv[2 * r + 1]; v[r][2] = kv[4 + 2 * r]; v[r][3] = kv[5 + 2 * r];
          v[r][4] = t < 2 ? kv[12 + 2 * r] : kv[8 + 2 * r]; v[r][5] = t < 2 ? kv[13 + 2 * r] : 0.f;
          v[r][6] = kv[24 + 2 * r]; v[r][7] = kv[25 + 2 * r]; v[r][8] = kv[28 + 2 * r]; v[r][9] = kv[29 + 2 * r];
          v[r][10] = t < 2 ? kv[16 + 2 * r] : kv[20 + 2 * r]; v[r][11] = t < 2 ? 0.f : kv[21 + 2 * r];
        }
        const uint32_t xa = sb + OFF_KX + w * 3072 + lane * 16;
        if (wg != rank) {
          const uint32_t ra = mapa(xa, wg), rb = mapa(sb + B_KX, wg);
#pragma unroll
          for (int r = 0; r < 2; r++)
            if (r == 0 || w < 2)
#pragma unroll
              for (int i = 0; i < 3; i++) st_async4(ra + r * 1536 + i * 512, v[r][4 * i], v[r][4 * i + 1], v[r][4 * i + 2], v[r][4 * i + 3], rb);
        } else {
          float* b0 = prm.s->kv + (cg * 2 + rank) * 2560 + w * 1024 + lane * 4;
          mbar_wait(sb + B_KX, 0);
          float4 u[2][3];
#pragma unroll
          for (int r = 0; r < 2; r++)
            if (r == 0 || w < 2)
#pragma unroll
              for (int i = 0; i < 3; i++) u[r][i] = lds128f(xa + r * 1536 + i * 512);
#pragma unroll
          for (int r = 0; r < 2; r++)
            if (r == 0 || w < 2) {
              float* b = b0 + r * 512;
              red4(b, v[r][0] + u[r][0].x, v[r][1] + u[r][0].y, v[r][2] + u[r][0].z);
              red4(b + 128, v[r][3] + u[r][0].w, v[r][4] + u[r][1].x, v[r][5] + u[r][1].y);
              red4(b + 256, v[r][6] + u[r][1].z, v[r][7] + u[r][1].w, v[r][8] + u[r][2].x);
              red4(b + 384, v[r][9] + u[r][2].y, v[r][10] + u[r][2].z, v[r][11] + u[r][2].w);
            }
          if (w == 0) STAMPW(98);
        }
      }
      __syncwarp();
      if (lane < 4) mbar_arrive_cl(sb + B_EMPTYO + 8 * (lane >> 1), lane & 1);
    }
    if (softmax_wide(softmax_row(pq, ph0) + softmax_row(pq + 2, ph1))) { softmax_neg(pq, ph0); softmax_neg(pq + 2, ph1); }
    reg_fence<20>(ph0); reg_fence<20>(ph1);
    STAMPW(24 + warp);
    {
      const int h = lane >> 3, fb = (lane >> 2) & 1;
      const float* src = prm.s->kv + (cg * 2 + (h >> 1)) * 2560 + (warp >> 2) * 512 + (h & 1) * 256 + ((2 * (warp & 3) + fb) * 4 + t) * 4;
      const int j0 = t + 2 * (h & 1), j2 = (h & 1) ? (t == 0 ? 10 : t - 2) : 8 + t;
      const bool has2 = t != ((h & 1) ? 1 : 3);
      const uint32_t dst = sb + OFF_KVB + warp * 128 + (2 * h + fb) * 16 + 4 * h;
      float4 f[3][2];
      int n = 0;
      while (true) {
        bool ok = true;
#pragma unroll
        for (int i = 0; i < 3; i++)
          if (i < 2 || warp < 4) { f[i][0] = ld_rlx4(src + i * 1024); f[i][1] = ld_rlx4(src + i * 1024 + 128); }
#pragma unroll
        for (int i = 0; i < 3; i++)
          if (i < 2 || warp < 4) ok = ok && f[i][0].w == 8.f && f[i][1].w == 8.f;
        if (__all_sync(0xffffffffu, ok)) break;
        if (++n > SPIN_MAX) __trap();
      }
      if (warp == 0) STAMPW(50);
#pragma unroll
      for (int i = 0; i < 3; i++)
        if (i < 2 || warp < 4) {
          sts32(dst + i * 1024 + j0 * KVB_S, pack(f[i][0].x, f[i][0].y));
          sts32(dst + i * 1024 + (j0 + 4) * KVB_S, pack(f[i][0].z, f[i][1].x));
          if (has2) sts32(dst + i * 1024 + j2 * KVB_S, pack(f[i][1].y, f[i][1].z));
        }
    }
    fence_lite(sb + B_T);
    bar_sync(1, 256);
    {
      float p[44];
      if (warp == 0) STAMPW(68);
      const uint64_t db = mkdesc(sb + OFF_KVB, 128, KVB_S, 0);
      wg_fence();
#pragma unroll
      for (int s = 0; s < 10; s++) wgmma_rs<88, 1>(p, ph0[2 * s], ph1[2 * s], ph0[2 * s + 1], ph1[2 * s + 1], db + 16 * s, s > 0);
      wg_commit();
      wg_wait<0>();
      reg_fence<44>(p);
      if (warp == 0) STAMPW(69);
      if (lane < 4) mbar_arrive_cl(sb + B_EMPTYO + 16 + 8 * (lane >> 1), lane & 1);
      const float r0 = rcp(p[40] + 1e-6f), r1 = rcp(p[42] + 1e-6f);
      uint32_t* o = (uint32_t*)(prm.s->o + (rt * 8 + cg) * 20480 + (8 * wg + 2 * w) * 128) + lane;
#pragma unroll
      for (int j = 0; j < 10; j++) {
        __stcg(o + j * 512, pack(p[4 * j] * r0, p[4 * j + 1] * r0));
        __stcg(o + j * 512 + 32, pack(p[4 * j + 2] * r1, p[4 * j + 3] * r1));
      }
      bar_arrive(2, 288);
    }
    if (warp == 0) STAMPW(51);
    float p[40];
#pragma unroll
    for (int i = 0; i < 40; i++) p[i] = 0.f;
    reg_fence<40>(p);
    mbar_wait(sb + B_G, 0);
    const float l0 = __uint_as_float(lds32(sb + OFF_G + warp * 64 + g * 8)), l1 = __uint_as_float(lds32(sb + OFF_G + warp * 64 + g * 8 + 4));
    float gq[2] = { rcp(1.f + ex2(-1.4426950408889634f * l0)), rcp(1.f + ex2(-1.4426950408889634f * l1))};
    uint32_t ad[2]; ad[0] = sb + OFF_KT + ((lane >> 4) * 8 + (lane & 7)) * 256 + (((8 * wg + 2 * w + ((lane >> 3) & 1)) ^ (lane & 7)) * 16);
    const uint32_t ob = sb + OFF_S + 20480 + warp * 2560;
    ad[1] = ob + (lane & 15) * 160 + (lane >> 4) * 16;
    reg_fence<2>(gq); reg_fence<2>(ad);
    mbar_wait(sb + B_WO, 0);
#pragma unroll 1
    for (int i = 0; i < 8; i++) {
      const int st = i & 3;
      const uint32_t oa = sb + (st < 2 ? OFF_S : OFF_PHI) + (st & 1) * 20480 + wg * 1024;
      const uint32_t wa = OFF_WO + (((i + 3) & 7) - 3) * 10240;
      const uint32_t ta = OFF_WOT + (i >> 2) * 10240 + (i & 3) * 32;
      const uint64_t da = mkdesc(oa, 2048, 128, 0);
      const uint64_t db = mkdesc(sb + wa, ta - wa, 1024, 1);
      mbar_wait_nt(sb + B_FULLO + 8 * st, i >> 2);
      if (warp == 0) STAMPW(52 + i);
      wg_fence();
#pragma unroll
      for (int ks = 0; ks < 5; ks++) wgmma_ss<80, 0, 1>(p, da + 256 * ks, db + 128 * ks, 1);
      wg_commit();
      wg_wait<1>();
      if (i > 0 && i < 7 && lane < 2) mbar_arrive_cl(sb + B_EMPTYO + 8 * ((i - 1) & 3), lane);
    }
    mbar_wait_nt(sb + B_Y, 0);
    mbar_wait_nt(sb + B_EMPTYO + 8, 0);
    uint4 yv[5];
#pragma unroll
    for (int j = 0; j < 5; j++) yv[j] = ldsm4t(ad[0] + j * 4096);
    wg_wait<0>();
    reg_fence<40>(p);
    if (warp == 0) STAMPW(60);
    if (warp == 0) STAMPW(61);
    {
      const float g0 = gq[0], g1 = gq[1];
      const uint32_t oa = ad[1];
#pragma unroll
      for (int j = 0; j < 5; j++) {
        const uint4 y = yv[j];
        const float* a = p + 8 * j;
        uint32_t o0 = pack(fmaf(g0, a[0] - blo(y.x), blo(y.x)), fmaf(g0, a[1] - bhi(y.x), bhi(y.x)));
        uint32_t o1 = pack(fmaf(g1, a[2] - blo(y.y), blo(y.y)), fmaf(g1, a[3] - bhi(y.y), bhi(y.y)));
        uint32_t o2 = pack(fmaf(g0, a[4] - blo(y.z), blo(y.z)), fmaf(g0, a[5] - bhi(y.z), bhi(y.z)));
        uint32_t o3 = pack(fmaf(g1, a[6] - blo(y.w), blo(y.w)), fmaf(g1, a[7] - bhi(y.w), bhi(y.w)));
        stsm4(oa + j * 32, o0, o1, o2, o3);
      }
      fence_lite(sb + B_T);
      __syncwarp();
      if (lane == 0) {
        tma_st2d(&tmOut, ob, 80 * ct3, 128 * rt3 + 16 * warp);
        asm volatile("cp.async.bulk.commit_group;\ncp.async.bulk.wait_group.read 0;" ::: "memory");
      }
    }
    STAMPW(32 + warp);
    }
  } else if (warp < 12) {
    const int w = warp & 3;
    bar_sync(15, 192);
    if (w == 0) STAMPW(92);
#define CS 1
    if (CS >= 1) mbar_wait(sb + B_T, 0);
    if (CS >= 2) mbar_wait(sb + B_EMPTY + 16, 0);
    uint32_t ka = sb + OFF_KT + 4 * (2064 - 16 * w - 2 * g + 4 * t);
    uint32_t fa[4][8];
    conv_ld<0>(ka, fa[0]); conv_ld<1>(ka, fa[1]);
#pragma unroll 1
    for (int j = 0; j < 5; j++) {
      float acc[64];
#pragma unroll
      for (int i = 0; i < 64; i++) acc[i] = 0.f;
      reg_fence<64>(acc);
      mbar_wait(sb + B_FULLU + 8 * (j & 1), (j >> 1) & 1);
      if (w == 0) STAMPW(70 + j);
      ConvLoop<0>::run(acc, ka, mkdesc(sb + OFF_U + (j & 1) * 4480, 2240, 128, 0), fa);
      ka += (j & 1) ? -8320 : 8320;
      wg_wait<0>();
      reg_fence<64>(acc);
      if (w == 0) STAMPW(75 + j);
      bar_sync(6, 192);
      conv_ld<0>(ka, fa[0]); conv_ld<1>(ka, fa[1]);
      put_compact(sb + OFF_U + (j & 1) * 4480, th, kr);
#pragma unroll
      for (int i = 0; i < 6; i++) kr[i] = kr[i + 3];
      const uint32_t pa = sb + OFF_P + w * 4096 + ((lane >> 3) & 1) * 2048 + ((lane >> 4) * 8 + (lane & 7)) * 16;
#pragma unroll
      for (int i = 0; i < 8; i++) {
        const float* a = acc + 8 * i;
        stsm4t(pa + i * 256, pack(a[0], a[1]), pack(a[2], a[3]), pack(a[4], a[5]), pack(a[6], a[7]));
      }
      bar_arrive(5, 192);
    }
  } else {
    asm volatile("setmaxnreg.dec.sync.aligned.u32 48;");
    if (warp == 12) {
      if (lane == 0) {
        asm volatile("prefetch.tensormap [%0];" ::"l"(&tmWo) : "memory");
        asm volatile("prefetch.tensormap [%0];" ::"l"(&tmOut) : "memory");
        mbar_wait(sb + B_FULL, 0);
        asm volatile("cp.async.bulk.prefetch.L2.global [%0], %1;" ::"l"((const char*)prm.w + 64 * KP * 3840 + cta * (10 - KP) * 1920), "n"((10 - KP) * 1920) : "memory");
        asm volatile("cp.async.bulk.prefetch.L2.global [%0], 6400;" ::"l"((const char*)prm.wo + cta * 6400) : "memory");
      }
      {
        const int kbl = kblock(lane + 3, cg);
        uint32_t st = sb + OFF_S, bar = sb + B_FULL, par = 0;
        const uint32_t go = 31744 + lane * 32 + (lane & 4) * 4;
#pragma unroll 1
        for (int p = 0; p < 7; p++) {
          const int k0 = 64 * __shfl_sync(0xffffffffu, kbl, p);
          const uint32_t gs = sb + OFF_S + (go ^ 16) + (k0 == 64 ? STG : (k0 >> 5) - 4);
          const uint32_t ga = lds16(gs), gb = lds16(gs + 16384);
          mbar_wait(bar + (B_EMPTY - B_FULL), par);
          sts16(st + go, ga); sts16(st + go + 16384, gb);
          __syncwarp();
          if (lane == 0) {
            STAMP(180 + p);
            mbar_expect(bar, STG_TX);
            tma2d(st, &tmX, k0, 128 * rt, bar);
            tma3d_mc(st + 16384 + rank * 16384, &tmW, 80 * cg, k0 + 32 * rank, 0, bar);
            tma3d_mc(st + 16384 + rank * 16384 + 12288, &tmWt, 80 * cg + 64, k0 + 32 * rank, 0, bar);
            STAMP(190 + p);
          }
          __syncwarp();
          if (st == sb + OFF_S + STG) { bar -= 16; par ^= 1; } else bar += 8;
          st = st == sb + OFF_S ? st + 2 * STG : st - STG;
        }
      }
      if (lane == 0) {
        const uint32_t wb = sb + B_WO;
        mbar_wait(sb + B_EMPTY + 8, 0);
        mbar_arrive(sb + B_T);
        mbar_expect(sb + B_G, 512);
        mbar_expect(wb, 20480);
        for (int u = 3; u < 5; u++) tma5d(sb + OFF_WO + u * 10240, &tmWo, 80 * ct3, 0, 0, 0, u, wb);
        mbar_wait(sb + B_EMPTY + 16, 0);
        mbar_expect(wb, 30720);
        for (int u = 0; u < 3; u++) tma5d(sb + OFF_WO + u * 10240, &tmWo, 80 * ct3, 0, 0, 0, u, wb);
      }
      __syncwarp();
      const unsigned ep1 = (ld_rlx(cnt + C_DONE * 32) >> 7) + 1;
      if (lane == 0) {
        const uint32_t wb = sb + B_WO;
        mbar_wait(sb + B_EMPTYO, 0);
        mbar_expect(wb, 30720);
        for (int u = 5; u < 8; u++) tma5d(sb + OFF_WO + (u - 8) * 10240, &tmWo, 80 * ct3, 0, 0, 0, u, wb);
      }
      __syncwarp();
      {
        unsigned ready = 0;
        int next = 0, n = 0;
        while (next < 8) {
          bool ok = false;
          if (lane < 8 && !((ready >> lane) & 1)) ok = (int)(ld_acq(cnt + (C_O + rt3) * 32 + lane) - ep1) >= 0;
          ready |= __ballot_sync(0xffffffffu, ok);
          while (next < 8 && ((ready >> next) & 1)) {
            if (lane == next) {
              const int st = next & 3;
              const uint32_t oa = sb + (st < 2 ? OFF_S : OFF_PHI) + (st & 1) * 20480;
              mbar_wait(sb + B_EMPTYO + 8 * st, next >> 2);
              fence_async_g();
              mbar_expect(sb + B_FULLO + 8 * st, 20480);
              bulk_ld_mc(oa + rank * 10240, prm.s->o + (rt3 * 8 + next) * 20480 + rank * 10240, 10240, sb + B_FULLO + 8 * st);
            }
            __syncwarp();
            next++;
          }
          if (++n > SPIN_MAX) __trap();
        }
      }
      if (lane == 0) {
        mbar_wait(sb + B_Y, 0);
        red_rlx(cnt + C_DONE * 32);
      }
    } else if (warp == 13) {
      const unsigned ep1 = (ld_rlx(cnt + C_DONE * 32) >> 7) + 1;
      {
        float4* z = (float4*)prm.s->kv + cg * 1280 + rt * 80;
        z[lane] = make_float4(0.f, 0.f, 0.f, 0.f); z[lane + 32] = make_float4(0.f, 0.f, 0.f, 0.f);
        if (lane < 16) z[lane + 64] = make_float4(0.f, 0.f, 0.f, 0.f);
      }
#pragma unroll
      for (int i = 0; i < 2; i++)
        if ((lane & 15) < 12) sts128(sb + OFF_U + (2 * i + (lane >> 4)) * 2240 + 2048 + (lane & 15) * 16, 0, 0, 0, 0);
      fence_async();
      bar_sync(8, 288);
      STAMPW(93);
      if (lane == 0) {
        red_rel(cnt + C_X * 32);
        STAMP(94);
      }
      bar_sync(7, 96);
      if (lane == 0) {
        poll(cnt + C_X * 32, 128 * ep1);
        mbar_arrive(sb + B_Z);
        fence_async_g();
        for (int j = 0; j < 2; j++) {
          const uint32_t bar = sb + B_FULLU + 8 * j, ub = sb + OFF_U + j * 4480;
          const unsigned char* src = prm.s->xT + (5 * cta + j) * 4096;
          mbar_expect(bar, 4096);
          bulk_ld(ub, src, 2048, bar);
          bulk_ld(ub + 2240, src + 2048, 2048, bar);
        }
      }
      __syncwarp();
      STAMPW(95);
      mbar_wait(sb + B_T, 0);
      {
        const int c = lane & 1, rr = lane >> 1;
        const uint16_t* src = prm.wo + (20 * ((rr >> 1) & 3) + 2 * (rr >> 3) + (rr & 1)) * 640 + 80 * ct3 + 64 + 8 * c;
#pragma unroll
        for (int q = 0; q < 4; q++) {
          const uint32_t d = sb + OFF_WOT + rr * 128 + (((2 * q + c) ^ (rr & 7)) * 16);
#pragma unroll
          for (int i = 0; i < 10; i++)
            asm volatile("cp.async.cg.shared.global [%0], [%1], 16;" ::"r"(d + (i / 5) * 10240 + (i % 5) * 2048), "l"(src + (80 * (q + 4 * (i / 5)) + 4 * (i % 5)) * 640) : "memory");
        }
      }
      asm volatile("cp.async.wait_all;" ::: "memory");
      fence_async();
      __syncwarp();
      if (lane == 0) mbar_arrive(sb + B_WO);
      STAMPW(97);
      bar_sync(2, 288);
      STAMPW(120);
      if (lane == 0) red_rel(cnt + (C_O + rt) * 32 + cg);
      STAMPW(121);
    } else {
      const int t64 = tid & 63;
#pragma unroll 1
      for (int j = -2; j < 5; j++) {
        const int ch = 5 * cta + j;
        bar_sync(j < 0 ? 19 + 8 * j : 5, 192);
        if (j < 3) {
          const int sl = j < 0 ? ~j : j & 1;
          const uint32_t kt = sb + OFF_KT + sl * 8320, ub = sb + OFF_U + sl * 4480;
          const uint32_t s4 = ub + 4 * t64, s8 = ub + 8 * t64;
          const uint32_t a0 = lds32(s4 + 1024), a1 = lds32(s4 + 1028), b0 = lds32(s4 + 768), b1 = lds32(s4 + 772);
          const uint32_t c0 = lds32(s4 + 512), c1 = lds32(s4 + 516), d0 = lds32(s8), d1 = lds32(s8 + 4), d2 = lds32(s8 + 8);
          const uint32_t a22 = prmt(a1, 0, 0x1010), a11 = prmt(a0, 0, 0x3232), a00 = prmt(a0, 0, 0x1010);
          const uint32_t b22 = prmt(b1, 0, 0x1010), b11 = prmt(b0, 0, 0x3232), c22 = prmt(c1, 0, 0x1010);
          sts128(kt + 8240 - 16 * t64, prmt(d2, d1, 0x7610), prmt(d2, 0, t64 == 63 ? 0x1010 : 0x1032), prmt(d1, d0, 0x7610), prmt(d1, 0, 0x1032));
          if (j >= 0) {
            bar_sync(13, 64);
            if (t64 == 0) {
              const uint32_t bar = sb + B_FULLU + 8 * sl;
              const unsigned char* src = prm.s->xT + (ch + 2) * 4096;
              fence_async_g();
              mbar_expect(bar, 4096);
              bulk_ld(ub, src, 2048, bar);
              bulk_ld(ub + 2240, src + 2048, 2048, bar);
            }
            __syncwarp();
          }
          sts128(kt + 4096 - 64 * t64, a22, a22, a22, a22);
          sts128(kt + 4112 - 64 * t64, prmt(a1, a0, 0x7610), a22, a11, a11);
          sts128(kt + 4128 - 64 * t64, a11, a11, a11, a11);
          sts128(kt + 4144 - 64 * t64, a00, prmt(a0, 0, 0x1032), a00, a00);
          sts128(kt + 6176 - 32 * t64, b22, b22, prmt(b1, b0, 0x7610), b22);
          sts128(kt + 6192 - 32 * t64, b11, b11, prmt(b0, 0, 0x1010), prmt(b0, 0, 0x1032));
          sts128(kt + 7216 - 16 * t64, c22, c22, prmt(c0, 0, 0x1032), prmt(c1, c0, 0x7610));
          if (t64 < 4) sts128(kt + 8256 + 16 * t64, t64 ? 0 : d0 & 0xFFFFu, t64 ? 0 : prmt(d0, 0, 0x1032), 0, 0);
          if (warp == 14) STAMPW(87 + j);
        }
        if (j == -2) continue;
        if (j == -1) {
          bar_arrive(15, 192);
          bar_arrive(7, 96);
          bar_arrive(6, 192);
          bar_sync(12, 192);
#pragma unroll 4
          for (int i = 0; i < 28; i++) sts128(sb + OFF_KVB + (i * 64 + t64) * 16, 0, 0, 0, 0);
          fence_lite(sb + B_T);
          __syncwarp();
          if (lane == 0) mbar_arrive(sb + B_Z);
          if (warp == 14) STAMPW(96);
          continue;
        }
#pragma unroll 1
        for (int it = 0; it < 2; it++) {
          const int th = t64 + 64 * it;
          uint4 e[4], o[4];
#pragma unroll
          for (int ww = 0; ww < 4; ww++) {
            const uint32_t pa = sb + OFF_P + ww * 4096 + (127 - th + ww) * 16, za = sb + OFF_U + 2048;
            e[ww] = lds128(th >= ww ? pa : za); o[ww] = lds128(th >= ww ? pa + 2048 : za);
          }
#define SUM4(a, c) hadd(hadd(a[0].c, a[1].c), hadd(a[2].c, a[3].c))
          unsigned char* yb = prm.s->y + ((th >> 3) * 640 + ch) * 256;
          const int c0 = 2 * (th & 7), sw = ch & 7;
          const uint32_t ex = SUM4(e, x), ey = SUM4(e, y), ez = SUM4(e, z), ew = SUM4(e, w), ox = SUM4(o, x), oy = SUM4(o, y), oz = SUM4(o, z), ow = SUM4(o, w);
          __stcg((uint4*)(yb + ((c0 ^ sw) * 16)), make_uint4(prmt(ex, ox, 0x5410), prmt(ex, ox, 0x7632), prmt(ey, oy, 0x5410), prmt(ey, oy, 0x7632)));
          __stcg((uint4*)(yb + (((c0 + 1) ^ sw) * 16)), make_uint4(prmt(ez, oz, 0x5410), prmt(ez, oz, 0x7632), prmt(ew, ow, 0x5410), prmt(ew, ow, 0x7632)));
        }
        if (j < 4) bar_arrive(6, 192);
        if (warp == 14) STAMPW(80 + j);
      }
      bar_sync(13, 64);
      if (lane == 0) {
        if (warp == 15) red_rel(cnt + (C_Y + (cta >> 4)) * 32);
        else {
          const unsigned ep1 = (ld_rlx(cnt + C_DONE * 32) >> 7) + 1;
          poll(cnt + (C_Y + ct3) * 32, 16 * ep1);
          fence_async_g();
          mbar_expect(sb + B_Y, 20480);
          bulk_ld(sb + OFF_KT, prm.s->y + (rt3 * 640 + 80 * ct3) * 256, 20480, sb + B_Y);
        }
      }
    }
  }
}

typedef CUresult (*EncFn)(CUtensorMap*, CUtensorMapDataType, cuuint32_t, void*, const cuuint64_t*, const cuuint64_t*, const cuuint32_t*,
                          const cuuint32_t*, CUtensorMapInterleave, CUtensorMapSwizzle, CUtensorMapL2promotion, CUtensorMapFloatOOBfill);
int enc(EncFn fn, CUtensorMap* m, void* p, int rank, const cuuint64_t* gd, const cuuint64_t* gs, const cuuint32_t* bd, CUtensorMapSwizzle sw) {
  const cuuint32_t es[5] = {1, 1, 1, 1, 1};
  return (int)fn(m, CU_TENSOR_MAP_DATA_TYPE_BFLOAT16, rank, p, gd, gs, bd, es, CU_TENSOR_MAP_INTERLEAVE_NONE, sw,
                 CU_TENSOR_MAP_L2_PROMOTION_L2_128B, CU_TENSOR_MAP_FLOAT_OOB_FILL_NONE);
}
int g_enc_err = 0;
}

extern "C" void kernel_launch(void* const* d_in, const int* in_sizes, int n_in, void* d_out, int out_size) {
  static EncFn fn = nullptr;
  static Scratch* scr = nullptr;
  if (!fn) {
    void* p = nullptr;
    cudaDriverEntryPointQueryResult qr;
    cudaGetDriverEntryPoint("cuTensorMapEncodeTiled", &p, cudaEnableDefault, &qr);
    fn = (EncFn)p;
    cudaGetSymbolAddress((void**)&scr, g_s);
    cudaFuncSetAttribute(fused_kernel, cudaFuncAttributeMaxDynamicSharedMemorySize, SMEM_BYTES + 512);
  }
  CUtensorMap mX, mW, mWt, mWo, mOut;
  int e = 0;
  { cuuint64_t gd[2] = {640, 2048}, gs[1] = {1280}; cuuint32_t bd[2] = {64, 128}; e |= enc(fn, &mX, d_in[0], 2, gd, gs, bd, CU_TENSOR_MAP_SWIZZLE_128B); }
  { cuuint64_t gd[3] = {640, 640, 3}, gs[2] = {3840, 1280}; cuuint32_t bd[3] = {64, 32, 3}; e |= enc(fn, &mW, d_in[1], 3, gd, gs, bd, CU_TENSOR_MAP_SWIZZLE_128B) << 4; }
  { cuuint64_t gd[3] = {640, 640, 3}, gs[2] = {3840, 1280}; cuuint32_t bd[3] = {16, 32, 3}; e |= enc(fn, &mWt, d_in[1], 3, gd, gs, bd, CU_TENSOR_MAP_SWIZZLE_32B) << 8; }
  { cuuint64_t gd[5] = {640, 2, 4, 10, 8}, gs[4] = {1280, 25600, 2560, 102400}; cuuint32_t bd[5] = {64, 2, 4, 10, 1}; e |= enc(fn, &mWo, d_in[3], 5, gd, gs, bd, CU_TENSOR_MAP_SWIZZLE_128B) << 12; }
  { cuuint64_t gd[2] = {640, 2048}, gs[1] = {1280}; cuuint32_t bd[2] = {80, 16}; e |= enc(fn, &mOut, d_out, 2, gd, gs, bd, CU_TENSOR_MAP_SWIZZLE_NONE) << 20; }
  g_enc_err = e;
  if (e) return;
  Params prm;
  prm.s = scr; prm.wo = (const uint16_t*)d_in[3]; prm.lar = (const uint16_t*)d_in[5]; prm.aim = (const uint16_t*)d_in[6];
  prm.cre = (const uint16_t*)d_in[7]; prm.cim = (const uint16_t*)d_in[8]; prm.ldt = (const uint16_t*)d_in[9]; prm.dsk = (const uint16_t*)d_in[10];
  prm.wphi = (const uint32_t*)d_in[2]; prm.gw = (const uint16_t*)d_in[11]; prm.x = (const uint4*)d_in[0]; prm.w = (const uint4*)d_in[1];
  fused_kernel<<<128, 512, SMEM_BYTES + 512, cudaStreamPerThread>>>(prm, mX, mW, mWt, mWo, mOut);
}
```
